```python
import torch

def _softmax(x, axis=-1):
    return torch.softmax(x, dim=axis)
def _gelu(x):
    return torch.nn.functional.gelu(x, approximate="tanh")
def _silu(x):
    return torch.nn.functional.silu(x)
def _sigmoid(x):
    return torch.sigmoid(x)
def _layernorm(x, axis=-1, eps=1e-5):
    m = x.mean(dim=axis, keepdim=True)
    v = x.var(dim=axis, keepdim=True, unbiased=False)
    return (x - m) / torch.sqrt(v + eps)
def _scatter_add(tgt, idx, src, axis=0):
    return tgt.clone().index_add_(axis, idx, src)
def _segment_sum(src, seg, n):
    out = torch.zeros((n,) + src.shape[1:], dtype=src.dtype)
    return out.index_add_(0, seg, src)
def _pad(x, pw):
    flat = tuple(v for pair in reversed(pw) for v in pair)
    return torch.nn.functional.pad(x, flat)

kernel_name = 'concat_heads__mha_block_cached__gqa_block_cached__near_ridge'

def setup_inputs():

    _w = (lambda a: (lambda t: t.to(torch.bfloat16) if t.is_floating_point() else t)(torch.as_tensor(a)))
    def _A_setup():
        B, Sq, D = 8, 96, 640
        H, Sk, Dh = 32, 96, 192
        return {
            "x": _w((lambda *s: torch.randn(*s, dtype=torch.bfloat16) * 0.8)(B, Sq, D)),
            "k_cache": _w((lambda *s: torch.randn(*s, dtype=torch.bfloat16) * 0.8)(B, H, Sk, Dh)),
            "v_cache": _w((lambda *s: torch.randn(*s, dtype=torch.bfloat16) * 0.05)(B, H, Sk, Dh)),
            "wq": _w((lambda *s: torch.randn(*s, dtype=torch.bfloat16) * 0.8)(D, H * Dh) * (D ** -0.5)),
            "wo": _w((lambda *s: torch.randn(*s, dtype=torch.bfloat16) * 0.05)(H * Dh, D) * ((H * Dh) ** -0.5)),
        }
    _A_in = _A_setup()

    def _B_setup():
        B, Sq, D = 8, 96, 640
        Hq, Hkv, Sk, Dh = 32, 32, 96, 192
        assert Hq % Hkv == 0, (Hq, Hkv)
        return {
            "x": _w((lambda *s: torch.randn(*s, dtype=torch.bfloat16) * 0.8)(B, Sq, D)),
            "k_cache": _w((lambda *s: torch.randn(*s, dtype=torch.bfloat16) * 0.8)(B, Hkv, Sk, Dh)),
            "v_cache": _w((lambda *s: torch.randn(*s, dtype=torch.bfloat16) * 0.05)(B, Hkv, Sk, Dh)),
            "wq": _w((lambda *s: torch.randn(*s, dtype=torch.bfloat16) * 0.8)(D, Hq * Dh) * (D ** -0.5)),
            "wo": _w((lambda *s: torch.randn(*s, dtype=torch.bfloat16) * 0.05)(Hq * Dh, D) * ((Hq * Dh) ** -0.5)),
        }
    _B_in = _B_setup()

    return {
        "A_x": _A_in["x"],
        "A_k_cache": _A_in["k_cache"],
        "A_v_cache": _A_in["v_cache"],
        "A_wq": _A_in["wq"],
        "A_wo": _A_in["wo"],
        "B_x": _B_in["x"],
        "B_k_cache": _B_in["k_cache"],
        "B_v_cache": _B_in["v_cache"],
        "B_wq": _B_in["wq"],
        "B_wo": _B_in["wo"],
    }

def reference(A_x, A_k_cache, A_v_cache, A_wq, A_wo, B_x, B_k_cache, B_v_cache, B_wq, B_wo):
    def _A_ref(x, k_cache, v_cache, wq, wo):
        B, Sq, D = x.shape
        H, Dh = 32, 192
        q = (lambda x, *d: x.permute(*d))((x @ wq).reshape(B, Sq, H, Dh), 0, 2, 1, 3)
        scores = torch.einsum("bhqd,bhkd->bhqk", q, k_cache) * (Dh ** -0.5)
        p = _softmax(scores, axis=-1)
        o = torch.einsum("bhqk,bhkd->bhqd", p, v_cache)
        return (lambda x, *d: x.permute(*d))(o, 0, 2, 1, 3).reshape(B, Sq, H * Dh) @ wo

    def _B_ref(x, k_cache, v_cache, wq, wo):
        B, Sq, D = x.shape
        Hq, Dh = 32, 192
        Hkv = k_cache.shape[1]
        rep = Hq // Hkv
        q = (lambda x, *d: x.permute(*d))((x @ wq).reshape(B, Sq, Hq, Dh), 0, 2, 1, 3)
        k = (lambda x, n, axis: torch.repeat_interleave(x, n, dim=axis))(k_cache, rep, axis=1)
        v = (lambda x, n, axis: torch.repeat_interleave(x, n, dim=axis))(v_cache, rep, axis=1)
        scores = torch.einsum("bhqd,bhkd->bhqk", q, k) * (Dh ** -0.5)
        p = _softmax(scores, axis=-1)
        o = torch.einsum("bhqk,bhkd->bhqd", p, v)
        return (lambda x, *d: x.permute(*d))(o, 0, 2, 1, 3).reshape(B, Sq, Hq * Dh) @ wo

    a = _A_ref(A_x, A_k_cache, A_v_cache, A_wq, A_wo)
    b = _B_ref(B_x, B_k_cache, B_v_cache, B_wq, B_wo)
    return torch.concatenate([a, b], axis=-1)
```

```cpp
#include <cuda_runtime.h>
#include <cuda_bf16.h>
#include <cuda.h>
#include <stdint.h>

namespace {

constexpr int NTHREADS   = 512;
constexpr int NSLOT      = 4;
constexpr int SLOT_BYTES = 49152;
constexpr int B_OFF      = 24576;
constexpr int KV_BYTES   = 36864;
constexpr int STG_BYTES  = 24576;
constexpr int SMEM_BYTES = NSLOT * SLOT_BYTES + STG_BYTES + 1024  ;

struct Params {
  CUtensorMap x[2], wq[2], k[2], v[2], wo[2];
  CUtensorMap o_st, o_ld;
};

__device__ __nv_bfloat16 g_O[1536 * 6144];
__device__ float4        g_part[128 * 3 * 5 * 384];
__device__ unsigned      g_ready[8 * 32];
__device__ unsigned      g_xflag[128 * 3];
__device__ unsigned      g_epoch;
__device__ unsigned      g_started;

__device__ __forceinline__ uint32_t smem_u32(const void* p) { return (uint32_t)__cvta_generic_to_shared(p); }
__device__ __forceinline__ void mbar_init(uint32_t bar, uint32_t count) {
  asm volatile("mbarrier.init.shared::cta.b64 [%0], %1;" :: "r"(bar), "r"(count) : "memory");
}
__device__ __forceinline__ void mbar_expect_tx(uint32_t bar, uint32_t bytes) {
  asm volatile("mbarrier.arrive.expect_tx.shared::cta.b64 _, [%0], %1;" :: "r"(bar), "r"(bytes) : "memory");
}
__device__ __forceinline__ void mbar_arrive_both(uint32_t bar) {
  asm volatile("{\n.reg .b32 r0, r1;\n"
               "mapa.shared::cluster.u32 r0, %0, 0;\n"
               "mapa.shared::cluster.u32 r1, %0, 1;\n"
               "mbarrier.arrive.shared::cluster.b64 _, [r0];\n"
               "mbarrier.arrive.shared::cluster.b64 _, [r1];\n}"
               :: "r"(bar) : "memory");
}
__device__ __forceinline__ void mbar_wait(uint32_t bar, uint32_t parity) {
  asm volatile("{\n.reg .pred P1;\n.reg .u32 cnt;\nmov.u32 cnt, 0;\n"
               "LAB_WAIT:\n"
               "mbarrier.try_wait.parity.shared::cta.b64 P1, [%0], %1;\n"
               "@P1 bra DONE;\n"
               "add.u32 cnt, cnt, 1;\n"
               "setp.lt.u32 P1, cnt, 16777216;\n"
               "@P1 bra LAB_WAIT;\n"
               "trap;\n"
               "DONE:\n}"
               :: "r"(bar), "r"(parity) : "memory");
}
__device__ __forceinline__ void tma_2d_mc(uint32_t dst, const CUtensorMap* m, uint32_t bar, int c0, int c1) {
  asm volatile("cp.async.bulk.tensor.2d.shared::cluster.global.mbarrier::complete_tx::bytes.multicast::cluster [%0], [%1, {%3, %4}], [%2], %5;"
               :: "r"(dst), "l"(m), "r"(bar), "r"(c0), "r"(c1), "h"((uint16_t)3) : "memory");
}
__device__ __forceinline__ void tma_3d(uint32_t dst, const CUtensorMap* m, uint32_t bar, int c0, int c1, int c2) {
  asm volatile("cp.async.bulk.tensor.3d.shared::cluster.global.mbarrier::complete_tx::bytes [%0], [%1, {%3, %4, %5}], [%2];"
               :: "r"(dst), "l"(m), "r"(bar), "r"(c0), "r"(c1), "r"(c2) : "memory");
}
__device__ __forceinline__ void tma_store_3d(const CUtensorMap* m, uint32_t src, int c0, int c1, int c2) {
  asm volatile("cp.async.bulk.tensor.3d.global.shared::cta.bulk_group [%0, {%2, %3, %4}], [%1];"
               :: "l"(m), "r"(src), "r"(c0), "r"(c1), "r"(c2) : "memory");
}
__device__ __forceinline__ void wg_fence()  { asm volatile("wgmma.fence.sync.aligned;" ::: "memory"); }
__device__ __forceinline__ void wg_commit() { asm volatile("wgmma.commit_group.sync.aligned;" ::: "memory"); }
template <int N> __device__ __forceinline__ void wg_wait() { asm volatile("wgmma.wait_group.sync.aligned %0;" :: "n"(N) : "memory"); }
__device__ __forceinline__ void bar_sync(int id, int n)   { asm volatile("bar.sync %0, %1;" :: "r"(id), "r"(n) : "memory"); }
__device__ __forceinline__ void bar_arrive(int id, int n) { asm volatile("bar.arrive %0, %1;" :: "r"(id), "r"(n) : "memory"); }
__device__ __forceinline__ void cluster_sync() {
  asm volatile("barrier.cluster.arrive.release.aligned;\nbarrier.cluster.wait.acquire.aligned;" ::: "memory");
}
__device__ __forceinline__ unsigned ld_acquire(const unsigned* p) {
  unsigned v; asm volatile("ld.acquire.gpu.global.u32 %0, [%1];" : "=r"(v) : "l"(p) : "memory"); return v;
}
__device__ __forceinline__ void red_release_add(unsigned* p, unsigned v) {
  asm volatile("red.release.gpu.global.add.u32 [%0], %1;" :: "l"(p), "r"(v) : "memory");
}
__device__ __forceinline__ void spin_until(const unsigned* p, unsigned target) {
  asm volatile("{\n.reg .pred P1;\n.reg .u32 cnt, v;\nmov.u32 cnt, 0;\n"
               "LAB_SPIN:\n"
               "ld.acquire.gpu.global.u32 v, [%0];\n"
               "sub.u32 v, v, %1;\n"
               "setp.ge.s32 P1, v, 0;\n"
               "@P1 bra DONE;\n"
               "add.u32 cnt, cnt, 1;\n"
               "setp.lt.u32 P1, cnt, 4194304;\n"
               "@P1 bra LAB_SPIN;\n"
               "trap;\n"
               "DONE:\n}"
               :: "l"(p), "r"(target) : "memory");
}
__device__ __forceinline__ uint32_t desc_lo(uint32_t addr, uint32_t lbo) { return ((addr & 0x3FFFF) >> 4) | ((lbo >> 4) << 16); }
__device__ __forceinline__ uint64_t desc(uint32_t lo, uint32_t byte_off = 0) {
  uint64_t d;
  asm("mov.b64 %0, {%1, %2};" : "=l"(d) : "r"(lo + (byte_off >> 4)), "r"(0x40000040u));
  return d;
}
__device__ __forceinline__ uint32_t pack_bf16(float lo, float hi) {
  uint32_t r; asm("cvt.rn.bf16x2.f32 %0, %1, %2;" : "=r"(r) : "f"(hi), "f"(lo)); return r;
}
__device__ __forceinline__ float ex2(float x) { float r; asm("ex2.approx.ftz.f32 %0, %1;" : "=f"(r) : "f"(x)); return r; }

__device__ __forceinline__ void wgmma_ss_n128_tb1(float (&d)[64], uint64_t descA, uint64_t descB) {
  asm volatile("{\n.reg .pred p;\n"
    "setp.ne.b32 p, 1, 0;\n"
    "wgmma.mma_async.sync.aligned.m64n128k16.f32.bf16.bf16 "
    "{%0, %1, %2, %3, %4, %5, %6, %7, %8, %9, %10, %11, %12, %13, %14, %15, "
    "%16, %17, %18, %19, %20, %21, %22, %23, %24, %25, %26, %27, %28, %29, %30, %31, "
    "%32, %33, %34, %35, %36, %37, %38, %39, %40, %41, %42, %43, %44, %45, %46, %47, "
    "%48, %49, %50, %51, %52, %53, %54, %55, %56, %57, %58, %59, %60, %61, %62, %63}, "
    "%64, %65, p, 1, 1, 0, 1;\n}\n"
    : "+f"(d[0]), "+f"(d[1]), "+f"(d[2]), "+f"(d[3]), "+f"(d[4]), "+f"(d[5]), "+f"(d[6]), "+f"(d[7]),
      "+f"(d[8]), "+f"(d[9]), "+f"(d[10]), "+f"(d[11]), "+f"(d[12]), "+f"(d[13]), "+f"(d[14]), "+f"(d[15]),
      "+f"(d[16]), "+f"(d[17]), "+f"(d[18]), "+f"(d[19]), "+f"(d[20]), "+f"(d[21]), "+f"(d[22]), "+f"(d[23]),
      "+f"(d[24]), "+f"(d[25]), "+f"(d[26]), "+f"(d[27]), "+f"(d[28]), "+f"(d[29]), "+f"(d[30]), "+f"(d[31]),
      "+f"(d[32]), "+f"(d[33]), "+f"(d[34]), "+f"(d[35]), "+f"(d[36]), "+f"(d[37]), "+f"(d[38]), "+f"(d[39]),
      "+f"(d[40]), "+f"(d[41]), "+f"(d[42]), "+f"(d[43]), "+f"(d[44]), "+f"(d[45]), "+f"(d[46]), "+f"(d[47]),
      "+f"(d[48]), "+f"(d[49]), "+f"(d[50]), "+f"(d[51]), "+f"(d[52]), "+f"(d[53]), "+f"(d[54]), "+f"(d[55]),
      "+f"(d[56]), "+f"(d[57]), "+f"(d[58]), "+f"(d[59]), "+f"(d[60]), "+f"(d[61]), "+f"(d[62]), "+f"(d[63])
    : "l"(descA), "l"(descB));
}

__device__ __forceinline__ void wgmma_ss_n128_tb1_init(float (&d)[64], uint64_t descA, uint64_t descB) {
  asm volatile("{\n.reg .pred p;\n"
    "setp.ne.b32 p, 0, 0;\n"
    "wgmma.mma_async.sync.aligned.m64n128k16.f32.bf16.bf16 "
    "{%0, %1, %2, %3, %4, %5, %6, %7, %8, %9, %10, %11, %12, %13, %14, %15, "
    "%16, %17, %18, %19, %20, %21, %22, %23, %24, %25, %26, %27, %28, %29, %30, %31, "
    "%32, %33, %34, %35, %36, %37, %38, %39, %40, %41, %42, %43, %44, %45, %46, %47, "
    "%48, %49, %50, %51, %52, %53, %54, %55, %56, %57, %58, %59, %60, %61, %62, %63}, "
    "%64, %65, p, 1, 1, 0, 1;\n}\n"
    : "=f"(d[0]), "=f"(d[1]), "=f"(d[2]), "=f"(d[3]), "=f"(d[4]), "=f"(d[5]), "=f"(d[6]), "=f"(d[7]),
      "=f"(d[8]), "=f"(d[9]), "=f"(d[10]), "=f"(d[11]), "=f"(d[12]), "=f"(d[13]), "=f"(d[14]), "=f"(d[15]),
      "=f"(d[16]), "=f"(d[17]), "=f"(d[18]), "=f"(d[19]), "=f"(d[20]), "=f"(d[21]), "=f"(d[22]), "=f"(d[23]),
      "=f"(d[24]), "=f"(d[25]), "=f"(d[26]), "=f"(d[27]), "=f"(d[28]), "=f"(d[29]), "=f"(d[30]), "=f"(d[31]),
      "=f"(d[32]), "=f"(d[33]), "=f"(d[34]), "=f"(d[35]), "=f"(d[36]), "=f"(d[37]), "=f"(d[38]), "=f"(d[39]),
      "=f"(d[40]), "=f"(d[41]), "=f"(d[42]), "=f"(d[43]), "=f"(d[44]), "=f"(d[45]), "=f"(d[46]), "=f"(d[47]),
      "=f"(d[48]), "=f"(d[49]), "=f"(d[50]), "=f"(d[51]), "=f"(d[52]), "=f"(d[53]), "=f"(d[54]), "=f"(d[55]),
      "=f"(d[56]), "=f"(d[57]), "=f"(d[58]), "=f"(d[59]), "=f"(d[60]), "=f"(d[61]), "=f"(d[62]), "=f"(d[63])
    : "l"(descA), "l"(descB));
}

__device__ __forceinline__ void wgmma_ss_n64_tb1(float (&d)[32], uint64_t descA, uint64_t descB) {
  asm volatile("{\n.reg .pred p;\n"
    "setp.ne.b32 p, 1, 0;\n"
    "wgmma.mma_async.sync.aligned.m64n64k16.f32.bf16.bf16 "
    "{%0, %1, %2, %3, %4, %5, %6, %7, %8, %9, %10, %11, %12, %13, %14, %15, "
    "%16, %17, %18, %19, %20, %21, %22, %23, %24, %25, %26, %27, %28, %29, %30, %31}, "
    "%32, %33, p, 1, 1, 0, 1;\n}\n"
    : "+f"(d[0]), "+f"(d[1]), "+f"(d[2]), "+f"(d[3]), "+f"(d[4]), "+f"(d[5]), "+f"(d[6]), "+f"(d[7]),
      "+f"(d[8]), "+f"(d[9]), "+f"(d[10]), "+f"(d[11]), "+f"(d[12]), "+f"(d[13]), "+f"(d[14]), "+f"(d[15]),
      "+f"(d[16]), "+f"(d[17]), "+f"(d[18]), "+f"(d[19]), "+f"(d[20]), "+f"(d[21]), "+f"(d[22]), "+f"(d[23]),
      "+f"(d[24]), "+f"(d[25]), "+f"(d[26]), "+f"(d[27]), "+f"(d[28]), "+f"(d[29]), "+f"(d[30]), "+f"(d[31])
    : "l"(descA), "l"(descB));
}

__device__ __forceinline__ void wgmma_ss_n64_tb1_init(float (&d)[32], uint64_t descA, uint64_t descB) {
  asm volatile("{\n.reg .pred p;\n"
    "setp.ne.b32 p, 0, 0;\n"
    "wgmma.mma_async.sync.aligned.m64n64k16.f32.bf16.bf16 "
    "{%0, %1, %2, %3, %4, %5, %6, %7, %8, %9, %10, %11, %12, %13, %14, %15, "
    "%16, %17, %18, %19, %20, %21, %22, %23, %24, %25, %26, %27, %28, %29, %30, %31}, "
    "%32, %33, p, 1, 1, 0, 1;\n}\n"
    : "=f"(d[0]), "=f"(d[1]), "=f"(d[2]), "=f"(d[3]), "=f"(d[4]), "=f"(d[5]), "=f"(d[6]), "=f"(d[7]),
      "=f"(d[8]), "=f"(d[9]), "=f"(d[10]), "=f"(d[11]), "=f"(d[12]), "=f"(d[13]), "=f"(d[14]), "=f"(d[15]),
      "=f"(d[16]), "=f"(d[17]), "=f"(d[18]), "=f"(d[19]), "=f"(d[20]), "=f"(d[21]), "=f"(d[22]), "=f"(d[23]),
      "=f"(d[24]), "=f"(d[25]), "=f"(d[26]), "=f"(d[27]), "=f"(d[28]), "=f"(d[29]), "=f"(d[30]), "=f"(d[31])
    : "l"(descA), "l"(descB));
}

__device__ __forceinline__ void wgmma_ss_n160_tb1(float (&d)[80], uint64_t descA, uint64_t descB) {
  asm volatile("{\n.reg .pred p;\n"
    "setp.ne.b32 p, 1, 0;\n"
    "wgmma.mma_async.sync.aligned.m64n160k16.f32.bf16.bf16 "
    "{%0, %1, %2, %3, %4, %5, %6, %7, %8, %9, %10, %11, %12, %13, %14, %15, "
    "%16, %17, %18, %19, %20, %21, %22, %23, %24, %25, %26, %27, %28, %29, %30, %31, "
    "%32, %33, %34, %35, %36, %37, %38, %39, %40, %41, %42, %43, %44, %45, %46, %47, "
    "%48, %49, %50, %51, %52, %53, %54, %55, %56, %57, %58, %59, %60, %61, %62, %63, "
    "%64, %65, %66, %67, %68, %69, %70, %71, %72, %73, %74, %75, %76, %77, %78, %79}, "
    "%80, %81, p, 1, 1, 0, 1;\n}\n"
    : "+f"(d[0]), "+f"(d[1]), "+f"(d[2]), "+f"(d[3]), "+f"(d[4]), "+f"(d[5]), "+f"(d[6]), "+f"(d[7]),
      "+f"(d[8]), "+f"(d[9]), "+f"(d[10]), "+f"(d[11]), "+f"(d[12]), "+f"(d[13]), "+f"(d[14]), "+f"(d[15]),
      "+f"(d[16]), "+f"(d[17]), "+f"(d[18]), "+f"(d[19]), "+f"(d[20]), "+f"(d[21]), "+f"(d[22]), "+f"(d[23]),
      "+f"(d[24]), "+f"(d[25]), "+f"(d[26]), "+f"(d[27]), "+f"(d[28]), "+f"(d[29]), "+f"(d[30]), "+f"(d[31]),
      "+f"(d[32]), "+f"(d[33]), "+f"(d[34]), "+f"(d[35]), "+f"(d[36]), "+f"(d[37]), "+f"(d[38]), "+f"(d[39]),
      "+f"(d[40]), "+f"(d[41]), "+f"(d[42]), "+f"(d[43]), "+f"(d[44]), "+f"(d[45]), "+f"(d[46]), "+f"(d[47]),
      "+f"(d[48]), "+f"(d[49]), "+f"(d[50]), "+f"(d[51]), "+f"(d[52]), "+f"(d[53]), "+f"(d[54]), "+f"(d[55]),
      "+f"(d[56]), "+f"(d[57]), "+f"(d[58]), "+f"(d[59]), "+f"(d[60]), "+f"(d[61]), "+f"(d[62]), "+f"(d[63]),
      "+f"(d[64]), "+f"(d[65]), "+f"(d[66]), "+f"(d[67]), "+f"(d[68]), "+f"(d[69]), "+f"(d[70]), "+f"(d[71]),
      "+f"(d[72]), "+f"(d[73]), "+f"(d[74]), "+f"(d[75]), "+f"(d[76]), "+f"(d[77]), "+f"(d[78]), "+f"(d[79])
    : "l"(descA), "l"(descB));
}

__device__ __forceinline__ void wgmma_ss_n160_tb1_init(float (&d)[80], uint64_t descA, uint64_t descB) {
  asm volatile("{\n.reg .pred p;\n"
    "setp.ne.b32 p, 0, 0;\n"
    "wgmma.mma_async.sync.aligned.m64n160k16.f32.bf16.bf16 "
    "{%0, %1, %2, %3, %4, %5, %6, %7, %8, %9, %10, %11, %12, %13, %14, %15, "
    "%16, %17, %18, %19, %20, %21, %22, %23, %24, %25, %26, %27, %28, %29, %30, %31, "
    "%32, %33, %34, %35, %36, %37, %38, %39, %40, %41, %42, %43, %44, %45, %46, %47, "
    "%48, %49, %50, %51, %52, %53, %54, %55, %56, %57, %58, %59, %60, %61, %62, %63, "
    "%64, %65, %66, %67, %68, %69, %70, %71, %72, %73, %74, %75, %76, %77, %78, %79}, "
    "%80, %81, p, 1, 1, 0, 1;\n}\n"
    : "=f"(d[0]), "=f"(d[1]), "=f"(d[2]), "=f"(d[3]), "=f"(d[4]), "=f"(d[5]), "=f"(d[6]), "=f"(d[7]),
      "=f"(d[8]), "=f"(d[9]), "=f"(d[10]), "=f"(d[11]), "=f"(d[12]), "=f"(d[13]), "=f"(d[14]), "=f"(d[15]),
      "=f"(d[16]), "=f"(d[17]), "=f"(d[18]), "=f"(d[19]), "=f"(d[20]), "=f"(d[21]), "=f"(d[22]), "=f"(d[23]),
      "=f"(d[24]), "=f"(d[25]), "=f"(d[26]), "=f"(d[27]), "=f"(d[28]), "=f"(d[29]), "=f"(d[30]), "=f"(d[31]),
      "=f"(d[32]), "=f"(d[33]), "=f"(d[34]), "=f"(d[35]), "=f"(d[36]), "=f"(d[37]), "=f"(d[38]), "=f"(d[39]),
      "=f"(d[40]), "=f"(d[41]), "=f"(d[42]), "=f"(d[43]), "=f"(d[44]), "=f"(d[45]), "=f"(d[46]), "=f"(d[47]),
      "=f"(d[48]), "=f"(d[49]), "=f"(d[50]), "=f"(d[51]), "=f"(d[52]), "=f"(d[53]), "=f"(d[54]), "=f"(d[55]),
      "=f"(d[56]), "=f"(d[57]), "=f"(d[58]), "=f"(d[59]), "=f"(d[60]), "=f"(d[61]), "=f"(d[62]), "=f"(d[63]),
      "=f"(d[64]), "=f"(d[65]), "=f"(d[66]), "=f"(d[67]), "=f"(d[68]), "=f"(d[69]), "=f"(d[70]), "=f"(d[71]),
      "=f"(d[72]), "=f"(d[73]), "=f"(d[74]), "=f"(d[75]), "=f"(d[76]), "=f"(d[77]), "=f"(d[78]), "=f"(d[79])
    : "l"(descA), "l"(descB));
}

__device__ __forceinline__ void wgmma_rs_n96_tb0(float (&d)[48], uint32_t a0, uint32_t a1, uint32_t a2, uint32_t a3, uint64_t descB) {
  asm volatile("{\n.reg .pred p;\n"
    "setp.ne.b32 p, 1, 0;\n"
    "wgmma.mma_async.sync.aligned.m64n96k16.f32.bf16.bf16 "
    "{%0, %1, %2, %3, %4, %5, %6, %7, %8, %9, %10, %11, %12, %13, %14, %15, "
    "%16, %17, %18, %19, %20, %21, %22, %23, %24, %25, %26, %27, %28, %29, %30, %31, "
    "%32, %33, %34, %35, %36, %37, %38, %39, %40, %41, %42, %43, %44, %45, %46, %47}, "
    "{%48, %49, %50, %51}, %52, p, 1, 1, 0;\n}\n"
    : "+f"(d[0]), "+f"(d[1]), "+f"(d[2]), "+f"(d[3]), "+f"(d[4]), "+f"(d[5]), "+f"(d[6]), "+f"(d[7]),
      "+f"(d[8]), "+f"(d[9]), "+f"(d[10]), "+f"(d[11]), "+f"(d[12]), "+f"(d[13]), "+f"(d[14]), "+f"(d[15]),
      "+f"(d[16]), "+f"(d[17]), "+f"(d[18]), "+f"(d[19]), "+f"(d[20]), "+f"(d[21]), "+f"(d[22]), "+f"(d[23]),
      "+f"(d[24]), "+f"(d[25]), "+f"(d[26]), "+f"(d[27]), "+f"(d[28]), "+f"(d[29]), "+f"(d[30]), "+f"(d[31]),
      "+f"(d[32]), "+f"(d[33]), "+f"(d[34]), "+f"(d[35]), "+f"(d[36]), "+f"(d[37]), "+f"(d[38]), "+f"(d[39]),
      "+f"(d[40]), "+f"(d[41]), "+f"(d[42]), "+f"(d[43]), "+f"(d[44]), "+f"(d[45]), "+f"(d[46]), "+f"(d[47])
    : "r"(a0), "r"(a1), "r"(a2), "r"(a3), "l"(descB));
}

__device__ __forceinline__ void wgmma_rs_n96_tb0_init(float (&d)[48], uint32_t a0, uint32_t a1, uint32_t a2, uint32_t a3, uint64_t descB) {
  asm volatile("{\n.reg .pred p;\n"
    "setp.ne.b32 p, 0, 0;\n"
    "wgmma.mma_async.sync.aligned.m64n96k16.f32.bf16.bf16 "
    "{%0, %1, %2, %3, %4, %5, %6, %7, %8, %9, %10, %11, %12, %13, %14, %15, "
    "%16, %17, %18, %19, %20, %21, %22, %23, %24, %25, %26, %27, %28, %29, %30, %31, "
    "%32, %33, %34, %35, %36, %37, %38, %39, %40, %41, %42, %43, %44, %45, %46, %47}, "
    "{%48, %49, %50, %51}, %52, p, 1, 1, 0;\n}\n"
    : "=f"(d[0]), "=f"(d[1]), "=f"(d[2]), "=f"(d[3]), "=f"(d[4]), "=f"(d[5]), "=f"(d[6]), "=f"(d[7]),
      "=f"(d[8]), "=f"(d[9]), "=f"(d[10]), "=f"(d[11]), "=f"(d[12]), "=f"(d[13]), "=f"(d[14]), "=f"(d[15]),
      "=f"(d[16]), "=f"(d[17]), "=f"(d[18]), "=f"(d[19]), "=f"(d[20]), "=f"(d[21]), "=f"(d[22]), "=f"(d[23]),
      "=f"(d[24]), "=f"(d[25]), "=f"(d[26]), "=f"(d[27]), "=f"(d[28]), "=f"(d[29]), "=f"(d[30]), "=f"(d[31]),
      "=f"(d[32]), "=f"(d[33]), "=f"(d[34]), "=f"(d[35]), "=f"(d[36]), "=f"(d[37]), "=f"(d[38]), "=f"(d[39]),
      "=f"(d[40]), "=f"(d[41]), "=f"(d[42]), "=f"(d[43]), "=f"(d[44]), "=f"(d[45]), "=f"(d[46]), "=f"(d[47])
    : "r"(a0), "r"(a1), "r"(a2), "r"(a3), "l"(descB));
}

__device__ __forceinline__ void wgmma_rs_n192_tb1(float (&d)[96], uint32_t a0, uint32_t a1, uint32_t a2, uint32_t a3, uint64_t descB) {
  asm volatile("{\n.reg .pred p;\n"
    "setp.ne.b32 p, 1, 0;\n"
    "wgmma.mma_async.sync.aligned.m64n192k16.f32.bf16.bf16 "
    "{%0, %1, %2, %3, %4, %5, %6, %7, %8, %9, %10, %11, %12, %13, %14, %15, "
    "%16, %17, %18, %19, %20, %21, %22, %23, %24, %25, %26, %27, %28, %29, %30, %31, "
    "%32, %33, %34, %35, %36, %37, %38, %39, %40, %41, %42, %43, %44, %45, %46, %47, "
    "%48, %49, %50, %51, %52, %53, %54, %55, %56, %57, %58, %59, %60, %61, %62, %63, "
    "%64, %65, %66, %67, %68, %69, %70, %71, %72, %73, %74, %75, %76, %77, %78, %79, "
    "%80, %81, %82, %83, %84, %85, %86, %87, %88, %89, %90, %91, %92, %93, %94, %95}, "
    "{%96, %97, %98, %99}, %100, p, 1, 1, 1;\n}\n"
    : "+f"(d[0]), "+f"(d[1]), "+f"(d[2]), "+f"(d[3]), "+f"(d[4]), "+f"(d[5]), "+f"(d[6]), "+f"(d[7]),
      "+f"(d[8]), "+f"(d[9]), "+f"(d[10]), "+f"(d[11]), "+f"(d[12]), "+f"(d[13]), "+f"(d[14]), "+f"(d[15]),
      "+f"(d[16]), "+f"(d[17]), "+f"(d[18]), "+f"(d[19]), "+f"(d[20]), "+f"(d[21]), "+f"(d[22]), "+f"(d[23]),
      "+f"(d[24]), "+f"(d[25]), "+f"(d[26]), "+f"(d[27]), "+f"(d[28]), "+f"(d[29]), "+f"(d[30]), "+f"(d[31]),
      "+f"(d[32]), "+f"(d[33]), "+f"(d[34]), "+f"(d[35]), "+f"(d[36]), "+f"(d[37]), "+f"(d[38]), "+f"(d[39]),
      "+f"(d[40]), "+f"(d[41]), "+f"(d[42]), "+f"(d[43]), "+f"(d[44]), "+f"(d[45]), "+f"(d[46]), "+f"(d[47]),
      "+f"(d[48]), "+f"(d[49]), "+f"(d[50]), "+f"(d[51]), "+f"(d[52]), "+f"(d[53]), "+f"(d[54]), "+f"(d[55]),
      "+f"(d[56]), "+f"(d[57]), "+f"(d[58]), "+f"(d[59]), "+f"(d[60]), "+f"(d[61]), "+f"(d[62]), "+f"(d[63]),
      "+f"(d[64]), "+f"(d[65]), "+f"(d[66]), "+f"(d[67]), "+f"(d[68]), "+f"(d[69]), "+f"(d[70]), "+f"(d[71]),
      "+f"(d[72]), "+f"(d[73]), "+f"(d[74]), "+f"(d[75]), "+f"(d[76]), "+f"(d[77]), "+f"(d[78]), "+f"(d[79]),
      "+f"(d[80]), "+f"(d[81]), "+f"(d[82]), "+f"(d[83]), "+f"(d[84]), "+f"(d[85]), "+f"(d[86]), "+f"(d[87]),
      "+f"(d[88]), "+f"(d[89]), "+f"(d[90]), "+f"(d[91]), "+f"(d[92]), "+f"(d[93]), "+f"(d[94]), "+f"(d[95])
    : "r"(a0), "r"(a1), "r"(a2), "r"(a3), "l"(descB));
}

__device__ __forceinline__ void wgmma_rs_n192_tb1_init(float (&d)[96], uint32_t a0, uint32_t a1, uint32_t a2, uint32_t a3, uint64_t descB) {
  asm volatile("{\n.reg .pred p;\n"
    "setp.ne.b32 p, 0, 0;\n"
    "wgmma.mma_async.sync.aligned.m64n192k16.f32.bf16.bf16 "
    "{%0, %1, %2, %3, %4, %5, %6, %7, %8, %9, %10, %11, %12, %13, %14, %15, "
    "%16, %17, %18, %19, %20, %21, %22, %23, %24, %25, %26, %27, %28, %29, %30, %31, "
    "%32, %33, %34, %35, %36, %37, %38, %39, %40, %41, %42, %43, %44, %45, %46, %47, "
    "%48, %49, %50, %51, %52, %53, %54, %55, %56, %57, %58, %59, %60, %61, %62, %63, "
    "%64, %65, %66, %67, %68, %69, %70, %71, %72, %73, %74, %75, %76, %77, %78, %79, "
    "%80, %81, %82, %83, %84, %85, %86, %87, %88, %89, %90, %91, %92, %93, %94, %95}, "
    "{%96, %97, %98, %99}, %100, p, 1, 1, 1;\n}\n"
    : "=f"(d[0]), "=f"(d[1]), "=f"(d[2]), "=f"(d[3]), "=f"(d[4]), "=f"(d[5]), "=f"(d[6]), "=f"(d[7]),
      "=f"(d[8]), "=f"(d[9]), "=f"(d[10]), "=f"(d[11]), "=f"(d[12]), "=f"(d[13]), "=f"(d[14]), "=f"(d[15]),
      "=f"(d[16]), "=f"(d[17]), "=f"(d[18]), "=f"(d[19]), "=f"(d[20]), "=f"(d[21]), "=f"(d[22]), "=f"(d[23]),
      "=f"(d[24]), "=f"(d[25]), "=f"(d[26]), "=f"(d[27]), "=f"(d[28]), "=f"(d[29]), "=f"(d[30]), "=f"(d[31]),
      "=f"(d[32]), "=f"(d[33]), "=f"(d[34]), "=f"(d[35]), "=f"(d[36]), "=f"(d[37]), "=f"(d[38]), "=f"(d[39]),
      "=f"(d[40]), "=f"(d[41]), "=f"(d[42]), "=f"(d[43]), "=f"(d[44]), "=f"(d[45]), "=f"(d[46]), "=f"(d[47]),
      "=f"(d[48]), "=f"(d[49]), "=f"(d[50]), "=f"(d[51]), "=f"(d[52]), "=f"(d[53]), "=f"(d[54]), "=f"(d[55]),
      "=f"(d[56]), "=f"(d[57]), "=f"(d[58]), "=f"(d[59]), "=f"(d[60]), "=f"(d[61]), "=f"(d[62]), "=f"(d[63]),
      "=f"(d[64]), "=f"(d[65]), "=f"(d[66]), "=f"(d[67]), "=f"(d[68]), "=f"(d[69]), "=f"(d[70]), "=f"(d[71]),
      "=f"(d[72]), "=f"(d[73]), "=f"(d[74]), "=f"(d[75]), "=f"(d[76]), "=f"(d[77]), "=f"(d[78]), "=f"(d[79]),
      "=f"(d[80]), "=f"(d[81]), "=f"(d[82]), "=f"(d[83]), "=f"(d[84]), "=f"(d[85]), "=f"(d[86]), "=f"(d[87]),
      "=f"(d[88]), "=f"(d[89]), "=f"(d[90]), "=f"(d[91]), "=f"(d[92]), "=f"(d[93]), "=f"(d[94]), "=f"(d[95])
    : "r"(a0), "r"(a1), "r"(a2), "r"(a3), "l"(descB));
}

struct Ring {
  uint32_t u;
  __device__ __forceinline__ uint32_t slot()  const { return u & (NSLOT - 1); }
  __device__ __forceinline__ uint32_t phase() const { return (u >> 2) & 1; }
  __device__ __forceinline__ uint32_t full(uint32_t full0)   const { return full0 + 8 * slot(); }
  __device__ __forceinline__ uint32_t empty(uint32_t full0)  const { return full0 + 8 * NSLOT + 8 * slot(); }
  __device__ __forceinline__ uint32_t addr(uint32_t ring)    const { return ring + slot() * SLOT_BYTES; }
  __device__ __forceinline__ Ring operator+(uint32_t d) const { return Ring{u + d}; }
};

__device__ __forceinline__ void softmax96(float (&s)[48], uint32_t (&p)[24]) {
  const float c = 0.07216878364870322f * 1.4426950408889634f;
  float m0 = s[0], m1 = s[2];
#pragma unroll
  for (int j = 0; j < 12; j++) {
    m0 = fmaxf(m0, fmaxf(s[4 * j], s[4 * j + 1]));
    m1 = fmaxf(m1, fmaxf(s[4 * j + 2], s[4 * j + 3]));
  }
  m0 = fmaxf(m0, __shfl_xor_sync(0xffffffffu, m0, 1));
  m1 = fmaxf(m1, __shfl_xor_sync(0xffffffffu, m1, 1));
  m0 = fmaxf(m0, __shfl_xor_sync(0xffffffffu, m0, 2));
  m1 = fmaxf(m1, __shfl_xor_sync(0xffffffffu, m1, 2));
  const float b0 = -m0 * c, b1 = -m1 * c;
  float l0 = 0.f, l1 = 0.f;
#pragma unroll
  for (int j = 0; j < 12; j++) {
    s[4 * j]     = ex2(fmaf(s[4 * j],     c, b0));
    s[4 * j + 1] = ex2(fmaf(s[4 * j + 1], c, b0));
    s[4 * j + 2] = ex2(fmaf(s[4 * j + 2], c, b1));
    s[4 * j + 3] = ex2(fmaf(s[4 * j + 3], c, b1));
    l0 += s[4 * j] + s[4 * j + 1];
    l1 += s[4 * j + 2] + s[4 * j + 3];
  }
  l0 += __shfl_xor_sync(0xffffffffu, l0, 1);
  l1 += __shfl_xor_sync(0xffffffffu, l1, 1);
  l0 += __shfl_xor_sync(0xffffffffu, l0, 2);
  l1 += __shfl_xor_sync(0xffffffffu, l1, 2);
  const float r0 = __fdividef(1.f, l0), r1 = __fdividef(1.f, l1);
#pragma unroll
  for (int j = 0; j < 12; j++) {
    p[2 * j]     = pack_bf16(s[4 * j] * r0,     s[4 * j + 1] * r0);
    p[2 * j + 1] = pack_bf16(s[4 * j + 2] * r1, s[4 * j + 3] * r1);
  }
}

template <bool INIT>
__device__ __forceinline__ void qk_mma(float (&s)[48], const uint32_t (&qf)[48], uint32_t sl) {
  const uint32_t d = desc_lo(sl, 16);
  if (INIT) wgmma_rs_n96_tb0_init(s, qf[0], qf[1], qf[2], qf[3], desc(d));
  else      wgmma_rs_n96_tb0(s, qf[0], qf[1], qf[2], qf[3], desc(d));
#pragma unroll
  for (int k = 1; k < 12; k++)
    wgmma_rs_n96_tb0(s, qf[4 * k], qf[4 * k + 1], qf[4 * k + 2], qf[4 * k + 3], desc(d, (k >> 2) * 12288 + (k & 3) * 32));
}
template <bool INIT>
__device__ __forceinline__ void pv_mma(float (&o)[96], const uint32_t (&pf)[24], uint32_t sl) {
  const uint32_t d = desc_lo(sl, 12288);
  if (INIT) wgmma_rs_n192_tb1_init(o, pf[0], pf[1], pf[2], pf[3], desc(d));
  else      wgmma_rs_n192_tb1(o, pf[0], pf[1], pf[2], pf[3], desc(d));
#pragma unroll
  for (int k = 1; k < 6; k++)
    wgmma_rs_n192_tb1(o, pf[4 * k], pf[4 * k + 1], pf[4 * k + 2], pf[4 * k + 3], desc(d, k * 2048));
}

__global__ void __cluster_dims__(2, 1, 1) __launch_bounds__(NTHREADS, 1)
fused_attn_kernel(const __grid_constant__ Params prm, __nv_bfloat16* __restrict__ out) {
  extern __shared__ uint8_t smem_raw[];
  __shared__ uint64_t s_bars[2 * NSLOT];
  __shared__ unsigned s_lock;
  __shared__ unsigned s_epoch;

  const uint32_t ring = (smem_u32(smem_raw) + 1023) & ~1023u;
  const uint32_t stg  = ring + NSLOT * SLOT_BYTES;
  const uint32_t full0 = smem_u32(&s_bars[0]);

  const int tid = threadIdx.x, lane = tid & 31;
  const int warp = __shfl_sync(0xffffffffu, tid >> 5, 0);
  const int cta = blockIdx.x, rank = cta & 1, cl = cta >> 1;
  const int grp = cl >> 3, prob = grp >> 2, bp = grp & 3, j8 = cl & 7;
  const int split = j8 >> 1, nchunk = 2 * (j8 & 1) + rank;

  if (tid == 0) {
#pragma unroll
    for (int s = 0; s < NSLOT; s++) { mbar_init(full0 + 8 * s, 1); mbar_init(full0 + 8 * NSLOT + 8 * s, 6); }
    s_lock = 0;
    asm volatile("fence.mbarrier_init.release.cluster;" ::: "memory");
    const unsigned e = ld_acquire(&g_epoch);
    s_epoch = e;
    __threadfence();
    if (atomicAdd(&g_started, 1u) == gridDim.x - 1) { g_started = 0; __threadfence(); g_epoch = e + 1; }
  }
  __syncthreads();
  cluster_sync();
  const unsigned target = 3u * (s_epoch + 1u);

  if (warp >= 12) {
    asm volatile("setmaxnreg.dec.sync.aligned.u32 32;");
    if (warp == 12) {
      if (lane == 0) {
        Ring r{0};
#pragma unroll 1
        for (int w = 0; w < 2; w++) {
          const int h = 16 * w + 2 * j8 + rank;
#pragma unroll 1
          for (int ks = 0; ks < 10; ks++) {
            const uint32_t fb = r.full(full0), sl = r.addr(ring);
            mbar_wait(r.empty(full0), r.phase() ^ 1);
            mbar_expect_tx(fb, SLOT_BYTES);
            tma_3d(sl + B_OFF, &prm.wq[prob], fb, 0, 64 * ks, 3 * h);
            tma_2d_mc(sl + rank * 12288, &prm.x[prob], fb, 64 * ks, 192 * bp + 96 * rank);
            r.u++;
          }
#pragma unroll 1
          for (int t = 0; t < 4; t++) {
            const uint32_t fb = r.full(full0), sl = r.addr(ring);
            mbar_wait(r.empty(full0), r.phase() ^ 1);
            mbar_expect_tx(fb, KV_BYTES);
            tma_3d(sl, (t < 2) ? &prm.k[prob] : &prm.v[prob], fb, 0, ((2 * bp + (t & 1)) * 32 + h) * 96, 0);
            r.u++;
          }
        }
#pragma unroll 1
        for (int hh = 0; hh < 8; hh++) {
          const int h = (hh >> 2) * 16 + 4 * split + (hh & 3);
#pragma unroll 1
          for (int c = 0; c < 3; c++) {
            const uint32_t fb = r.full(full0), sl = r.addr(ring);
            const int k0 = h * 192 + c * 64;
            mbar_wait(r.empty(full0), r.phase() ^ 1);
            mbar_expect_tx(fb, SLOT_BYTES);
            tma_3d(sl + B_OFF,         &prm.wo[prob], fb, 0,   nchunk, k0);
            tma_3d(sl + B_OFF + 8192,  &prm.wo[prob], fb, 64,  nchunk, k0);
            tma_3d(sl + B_OFF + 16384, &prm.wo[prob], fb, 128, nchunk, k0);
            if (c == 0) {
              spin_until(&g_ready[grp * 32 + h], target);
              asm volatile("fence.proxy.async;" ::: "memory");
            }
            tma_2d_mc(sl + rank * 12288, &prm.o_ld, fb, k0, prob * 768 + 192 * bp + 96 * rank);
            r.u++;
          }
        }
      }
    } else {
      const int wg = warp - 13;
#pragma unroll 1
      for (int w = 0; w < 2; w++) {
        const int h = 16 * w + 2 * j8 + rank;
        bar_sync(4 + wg, 160);
        if (lane == 0) {
          tma_store_3d(&prm.o_st, stg, 0, prob * 768 + 192 * bp + 64 * wg, 3 * h);
          asm volatile("cp.async.bulk.commit_group;" ::: "memory");
          asm volatile("cp.async.bulk.wait_group.read 0;" ::: "memory");
          asm volatile("st.volatile.shared.u32 [%0], %1;" :: "r"(smem_u32(&s_lock)), "r"(0u) : "memory");
          asm volatile("cp.async.bulk.wait_group 0;" ::: "memory");
          asm volatile("fence.proxy.async;" ::: "memory");
          __threadfence();
          red_release_add(&g_ready[grp * 32 + h], 1u);
        }
        __syncwarp();
      }
    }
  } else {
    asm volatile("setmaxnreg.inc.sync.aligned.u32 160;");
    const int wg = warp >> 2, wq4 = warp & 3;
    const bool elected = (tid & 127) == 0;
    const uint32_t descA0 = desc_lo(ring + wg * 8192, 16), descB0 = desc_lo(ring + B_OFF, 8192);
    Ring r{0};

#pragma unroll 1
    for (int w = 0; w < 2; w++) {
      uint32_t qf[48];
      {
        float accA[64], accB[32];
        {
          const uint32_t da = descA0 + r.slot() * (SLOT_BYTES >> 4), db = descB0 + r.slot() * (SLOT_BYTES >> 4);
          mbar_wait(r.full(full0), r.phase());
          wg_fence();
          wgmma_ss_n128_tb1_init(accA, desc(da), desc(db));
          wgmma_ss_n64_tb1_init(accB, desc(da), desc(db, 16384));
#pragma unroll
          for (int k = 1; k < 4; k++) {
            wgmma_ss_n128_tb1(accA, desc(da, k * 32), desc(db, k * 2048));
            wgmma_ss_n64_tb1(accB, desc(da, k * 32), desc(db, 16384 + k * 2048));
          }
          wg_commit();
          r.u++;
        }
#pragma unroll 1
        for (int ks = 1; ks < 10; ks++) {
          const uint32_t da = descA0 + r.slot() * (SLOT_BYTES >> 4), db = descB0 + r.slot() * (SLOT_BYTES >> 4);
          mbar_wait(r.full(full0), r.phase());
          wg_fence();
#pragma unroll
          for (int k = 0; k < 4; k++) {
            wgmma_ss_n128_tb1(accA, desc(da, k * 32), desc(db, k * 2048));
            wgmma_ss_n64_tb1(accB, desc(da, k * 32), desc(db, 16384 + k * 2048));
          }
          wg_commit();
          wg_wait<1>();
          if (elected) mbar_arrive_both(Ring{r.u - 1}.empty(full0));
          r.u++;
        }
        wg_wait<0>();
        if (elected) mbar_arrive_both(Ring{r.u - 1}.empty(full0));
#pragma unroll
        for (int i = 0; i < 16; i++) qf[32 + i] = pack_bf16(accB[2 * i], accB[2 * i + 1]);
#pragma unroll
        for (int i = 0; i < 32; i++) qf[i] = pack_bf16(accA[2 * i], accA[2 * i + 1]);
      }
      const Ring rK0 = r, rK1 = r + 1, rV0 = r + 2, rV1 = r + 3;
      r.u += 4;
      uint32_t pf[24];
      if (wg != 1) {
        const Ring mine = wg == 0 ? rK0 : rK1;
        float s[48];
        if (wg == 2) { mbar_wait(rK0.full(full0), rK0.phase()); if (elected) mbar_arrive_both(rK0.empty(full0)); }
        mbar_wait(mine.full(full0), mine.phase());
        const uint32_t sl = mine.addr(ring);
        wg_fence();
        qk_mma<true>(s, qf, sl);
        wg_commit();
        wg_wait<0>();
        if (elected) mbar_arrive_both(mine.empty(full0));
        softmax96(s, pf);
        if (wg == 0) { mbar_wait(rK1.full(full0), rK1.phase()); if (elected) mbar_arrive_both(rK1.empty(full0)); }
      } else {
        float s0[48];
        mbar_wait(rK0.full(full0), rK0.phase());
        wg_fence();
        qk_mma<true>(s0, qf, rK0.addr(ring));
        wg_commit();
        mbar_wait(rK1.full(full0), rK1.phase());
        wg_wait<0>();
        if (elected) mbar_arrive_both(rK0.empty(full0));
        if (wq4 < 2) {
#pragma unroll
          for (int i = 0; i < 48; i++) qf[i] = 0u;
        } else {
#pragma unroll
          for (int i = 0; i < 48; i++) s0[i] = 0.f;
        }
        wg_fence();
        qk_mma<false>(s0, qf, rK1.addr(ring));
        wg_commit();
        wg_wait<0>();
        if (elected) mbar_arrive_both(rK1.empty(full0));
        softmax96(s0, pf);
      }
      float o[96];
      if (wg != 1) {
        const Ring mine = wg == 0 ? rV0 : rV1;
        if (wg == 2) { mbar_wait(rV0.full(full0), rV0.phase()); if (elected) mbar_arrive_both(rV0.empty(full0)); }
        mbar_wait(mine.full(full0), mine.phase());
        const uint32_t sl = mine.addr(ring);
        wg_fence();
        pv_mma<true>(o, pf, sl);
        wg_commit();
        wg_wait<0>();
        if (elected) mbar_arrive_both(mine.empty(full0));
        if (wg == 0) { mbar_wait(rV1.full(full0), rV1.phase()); if (elected) mbar_arrive_both(rV1.empty(full0)); }
      } else {
        mbar_wait(rV0.full(full0), rV0.phase());
        wg_fence();
        pv_mma<true>(o, pf, rV0.addr(ring));
        wg_commit();
        mbar_wait(rV1.full(full0), rV1.phase());
        wg_wait<0>();
        if (elected) mbar_arrive_both(rV0.empty(full0));
        if (wq4 < 2) {
#pragma unroll
          for (int i = 0; i < 24; i++) pf[i] = 0u;
        } else {
#pragma unroll
          for (int i = 0; i < 96; i++) o[i] = 0.f;
        }
        wg_fence();
        pv_mma<false>(o, pf, rV1.addr(ring));
        wg_commit();
        wg_wait<0>();
        if (elected) mbar_arrive_both(rV1.empty(full0));
      }
      if (elected) {
        asm volatile("{\n.reg .pred P1;\n.reg .u32 cnt, v;\nmov.u32 cnt, 0;\n"
                     "LAB_LOCK:\n"
                     "atom.shared.cas.b32 v, [%0], 0, 1;\n"
                     "setp.eq.u32 P1, v, 0;\n"
                     "@P1 bra DONE;\n"
                     "add.u32 cnt, cnt, 1;\n"
                     "setp.lt.u32 P1, cnt, 16777216;\n"
                     "@P1 bra LAB_LOCK;\n"
                     "trap;\n"
                     "DONE:\n}" :: "r"(smem_u32(&s_lock)) : "memory");
      }
      bar_sync(1 + wg, 128);
      {
        const int row = 16 * wq4 + ((lane >> 3) & 1) * 8 + (lane & 7);
        const uint32_t base = stg + row * 128;
#pragma unroll
        for (int jj = 0; jj < 12; jj++) {
          const int blk = 2 * jj + (lane >> 4);
          const uint32_t addr = base + (jj >> 2) * 8192 + (((blk & 7) ^ (lane & 7)) << 4);
          asm volatile("stmatrix.sync.aligned.m8n8.x4.shared.b16 [%0], {%1, %2, %3, %4};"
                       :: "r"(addr), "r"(pack_bf16(o[8 * jj], o[8 * jj + 1])), "r"(pack_bf16(o[8 * jj + 2], o[8 * jj + 3])),
                          "r"(pack_bf16(o[8 * jj + 4], o[8 * jj + 5])), "r"(pack_bf16(o[8 * jj + 6], o[8 * jj + 7])) : "memory");
        }
      }
      asm volatile("fence.proxy.async.shared::cta;" ::: "memory");
      bar_arrive(4 + wg, 160);
    }

    float acc[80];
    {
      {
        const uint32_t da = descA0 + r.slot() * (SLOT_BYTES >> 4), db = descB0 + r.slot() * (SLOT_BYTES >> 4);
        mbar_wait(r.full(full0), r.phase());
        wg_fence();
        wgmma_ss_n160_tb1_init(acc, desc(da), desc(db));
#pragma unroll
        for (int k = 1; k < 4; k++) wgmma_ss_n160_tb1(acc, desc(da, k * 32), desc(db, k * 2048));
        wg_commit();
        r.u++;
      }
#pragma unroll 1
      for (int ks = 1; ks < 24; ks++) {
        const uint32_t da = descA0 + r.slot() * (SLOT_BYTES >> 4), db = descB0 + r.slot() * (SLOT_BYTES >> 4);
        mbar_wait(r.full(full0), r.phase());
        wg_fence();
#pragma unroll
        for (int k = 0; k < 4; k++) wgmma_ss_n160_tb1(acc, desc(da, k * 32), desc(db, k * 2048));
        wg_commit();
        wg_wait<1>();
        if (elected) mbar_arrive_both(Ring{r.u - 1}.empty(full0));
        r.u++;
      }
      wg_wait<0>();
      if (elected) mbar_arrive_both(Ring{r.u - 1}.empty(full0));
    }
    {
      const int t = tid;
#pragma unroll
      for (int q = 0; q < 4; q++) {
        if (q != split) {
          const int dcta = (grp * 8 + 2 * q + (j8 & 1)) * 2 + rank;
          const int srcslot = split < q ? split : split - 1;
          float4* dst = g_part + ((size_t)(dcta * 3 + srcslot) * 5) * 384 + t;
#pragma unroll
          for (int i = 0; i < 5; i++)
            __stcg(dst + i * 384, make_float4(acc[20 * q + 4 * i], acc[20 * q + 4 * i + 1], acc[20 * q + 4 * i + 2], acc[20 * q + 4 * i + 3]));
        }
      }
      __threadfence();
      bar_sync(1 + wg, 128);
      if ((tid & 127) < 4 && (tid & 127) != split) {
        const int q = tid & 127;
        const int dcta = (grp * 8 + 2 * q + (j8 & 1)) * 2 + rank;
        red_release_add(&g_xflag[dcta * 3 + wg], 1u);
      }
      float own[20];
#pragma unroll
      for (int i = 0; i < 20; i++)
        own[i] = split == 0 ? acc[i] : split == 1 ? acc[20 + i] : split == 2 ? acc[40 + i] : acc[60 + i];
      if (elected) spin_until(&g_xflag[cta * 3 + wg], target);
      bar_sync(1 + wg, 128);
      const float4* src = g_part + ((size_t)(cta * 3) * 5) * 384 + t;
#pragma unroll
      for (int sidx = 0; sidx < 3; sidx++) {
#pragma unroll
        for (int i = 0; i < 5; i++) {
          const float4 v = __ldcg(src + (sidx * 5 + i) * 384);
          own[4 * i] += v.x; own[4 * i + 1] += v.y; own[4 * i + 2] += v.z; own[4 * i + 3] += v.w;
        }
      }
      const int row = 192 * bp + 64 * wg + 16 * wq4 + (lane >> 2);
      __nv_bfloat16* op = out + (size_t)row * 1280 + 640 * prob + 160 * nchunk + 40 * split + 2 * (lane & 3);
#pragma unroll
      for (int i = 0; i < 5; i++) {
        *reinterpret_cast<uint32_t*>(op + 8 * i)            = pack_bf16(own[4 * i],     own[4 * i + 1]);
        *reinterpret_cast<uint32_t*>(op + 8 * 1280 + 8 * i) = pack_bf16(own[4 * i + 2], own[4 * i + 3]);
      }
    }
  }
  __syncthreads();
  cluster_sync();
}

typedef CUresult (*EncodeFn)(CUtensorMap*, CUtensorMapDataType, cuuint32_t, void*, const cuuint64_t*, const cuuint64_t*,
                             const cuuint32_t*, const cuuint32_t*, CUtensorMapInterleave, CUtensorMapSwizzle,
                             CUtensorMapL2promotion, CUtensorMapFloatOOBfill);

void make_map(EncodeFn enc, CUtensorMap* m, const void* ptr, int rank, const uint64_t* dims, const uint64_t* strides,
              const uint32_t* box) {
  cuuint64_t d[3], s[2]; cuuint32_t b[3], e[3] = {1, 1, 1};
  for (int i = 0; i < rank; i++) { d[i] = dims[i]; b[i] = box[i]; }
  for (int i = 0; i + 1 < rank; i++) s[i] = strides[i];
  enc(m, CU_TENSOR_MAP_DATA_TYPE_BFLOAT16, rank, const_cast<void*>(ptr), d, s, b, e, CU_TENSOR_MAP_INTERLEAVE_NONE,
      CU_TENSOR_MAP_SWIZZLE_128B, CU_TENSOR_MAP_L2_PROMOTION_L2_128B, CU_TENSOR_MAP_FLOAT_OOB_FILL_NONE);
}

}

extern "C" void kernel_launch(void* const* d_in, const int* in_sizes, int n_in, void* d_out, int out_size) {
  (void)in_sizes; (void)n_in; (void)out_size;
  static EncodeFn enc = nullptr;
  static void* o_ptr = nullptr;
  if (!enc) {
    void* fn = nullptr; cudaDriverEntryPointQueryResult st;
    cudaGetDriverEntryPoint("cuTensorMapEncodeTiled", &fn, cudaEnableDefault, &st);
    enc = (EncodeFn)fn;
    cudaGetSymbolAddress(&o_ptr, g_O);
    cudaFuncSetAttribute(fused_attn_kernel, cudaFuncAttributeMaxDynamicSharedMemorySize, SMEM_BYTES);
  }
  Params prm;
  for (int p = 0; p < 2; p++) {
    const void* x = d_in[5 * p + 0]; const void* k = d_in[5 * p + 1]; const void* v = d_in[5 * p + 2];
    const void* wq = d_in[5 * p + 3]; const void* wo = d_in[5 * p + 4];
    { uint64_t d[2] = {640, 768}, s[1] = {1280};              uint32_t b[2] = {64, 96};    make_map(enc, &prm.x[p],  x,  2, d, s, b); }
    { uint64_t d[3] = {64, 640, 96}, s[2] = {12288, 128};     uint32_t b[3] = {64, 64, 3}; make_map(enc, &prm.wq[p], wq, 3, d, s, b); }
    { uint64_t d[3] = {64, 24576, 3}, s[2] = {384, 128};      uint32_t b[3] = {64, 96, 3}; make_map(enc, &prm.k[p],  k,  3, d, s, b); }
    { uint64_t d[3] = {64, 24576, 3}, s[2] = {384, 128};      uint32_t b[3] = {64, 96, 3}; make_map(enc, &prm.v[p],  v,  3, d, s, b); }
    { uint64_t d[3] = {160, 4, 6144}, s[2] = {320, 1280};     uint32_t b[3] = {64, 1, 64}; make_map(enc, &prm.wo[p], wo, 3, d, s, b); }
  }
  { uint64_t d[3] = {64, 1536, 96}, s[2] = {12288, 128}; uint32_t b[3] = {64, 64, 3}; make_map(enc, &prm.o_st, o_ptr, 3, d, s, b); }
  { uint64_t d[2] = {6144, 1536}, s[1] = {12288};        uint32_t b[2] = {64, 96};    make_map(enc, &prm.o_ld, o_ptr, 2, d, s, b); }
  fused_attn_kernel<<<128, NTHREADS, SMEM_BYTES>>>(prm, (__nv_bfloat16*)d_out);
}
```

```cpp
#include <cuda_runtime.h>
#include <cuda_bf16.h>
#include <cuda.h>
#include <stdint.h>

namespace {

#define POL_STREAM policy_evict_first
#define USE_MAP 1
#define FL_LAG 0
#define FL_B1 2
#define FL_B2 4
#define FL_LD 6
#define FL2_LAG 0
#define FL2_B1 2
#define FL2_B2 5
#define FL2_LD 8
#define ORDER 1
#define PF_SKIP 0
#define PF_WO_N 0
#define ISSUE_Q 0
#define PF_MODE 1
#define PF_WIN 10
#define PF_R0 0
#define PF_R1 8
#define PF_R2 11
#define PF_R3 21
#define PF_R4 34
#define PF_DELAY_NS 500
constexpr int NTHREADS   = 512;
constexpr int NSLOT      = 4;
constexpr int SLOT_BYTES = 49152;
constexpr int B_OFF      = 24576;
constexpr int KV_BYTES   = 36864;
constexpr int STG_BYTES  = 3 * 8192;
constexpr int SMEM_BYTES = NSLOT * SLOT_BYTES + STG_BYTES + 1024  ;

struct Params {
  CUtensorMap x[2], wq[2], k[2], k1[2], v[2], v1[2], wo[2];
  CUtensorMap o_st, o_ld;
  const uint8_t* kptr[2];
  const uint8_t* vptr[2];
  const uint8_t* xptr[2];
  const uint8_t* wqptr[2];
  const uint8_t* woptr[2];
};

__constant__ uint8_t c_cluster_map[64] = {0, 8, 16, 24, 1, 2, 4, 32, 34, 36, 6, 38, 9, 10, 12, 40, 42, 44, 14, 46, 17, 18, 20, 48, 50, 52, 22, 54, 25, 26, 28, 56, 58, 60, 30, 62, 3, 5, 33, 35, 37, 7, 39, 11, 13, 41, 43, 45, 15, 47, 19, 21, 49, 51, 53, 23, 55, 27, 29, 57, 59, 61, 31, 63};

__device__ __nv_bfloat16 g_O[1536 * 6144];
constexpr int PART_BYTES = 384 * 40;
__device__ __align__(16) uint8_t g_part[128 * 3 * PART_BYTES];
__device__ unsigned      g_ready[8 * 32];
__device__ unsigned      g_xflag[128 * 3];
__device__ unsigned      g_epoch[128];

#define TR_DECL
#define TR(role, tag)
#define TR_WG(tag)
#define PROF(role, ev)
#define PROF_WG(ev)
#define PROF_USE(kind, u)
#define PROF_USE_WG(kind, u)

__device__ __forceinline__ uint32_t smem_u32(const void* p) { return (uint32_t)__cvta_generic_to_shared(p); }
__device__ __forceinline__ void mbar_init(uint32_t bar, uint32_t count) {
  asm volatile("mbarrier.init.shared::cta.b64 [%0], %1;" :: "r"(bar), "r"(count) : "memory");
}
__device__ __forceinline__ void mbar_expect_tx(uint32_t bar, uint32_t bytes) {
  asm volatile("mbarrier.arrive.expect_tx.shared::cta.b64 _, [%0], %1;" :: "r"(bar), "r"(bytes) : "memory");
}
__device__ __forceinline__ void mbar_arrive_both(uint32_t bar) {
  asm volatile("{\n.reg .b32 r0, r1;\n"
               "mapa.shared::cluster.u32 r0, %0, 0;\n"
               "mapa.shared::cluster.u32 r1, %0, 1;\n"
               "mbarrier.arrive.shared::cluster.b64 _, [r0];\n"
               "mbarrier.arrive.shared::cluster.b64 _, [r1];\n}"
               :: "r"(bar) : "memory");
}
__device__ __forceinline__ void mbar_wait(uint32_t bar, uint32_t parity) {
  asm volatile("{\n.reg .pred P1;\n.reg .u32 cnt;\nmov.u32 cnt, 0;\n"
               "LAB_WAIT:\n"
               "mbarrier.try_wait.parity.shared::cta.b64 P1, [%0], %1;\n"
               "@P1 bra DONE;\n"
               "add.u32 cnt, cnt, 1;\n"
               "setp.lt.u32 P1, cnt, 16777216;\n"
               "@P1 bra LAB_WAIT;\n"
               "trap;\n"
               "DONE:\n}"
               :: "r"(bar), "r"(parity) : "memory");
}
__device__ __forceinline__ uint64_t policy_evict_first() {
  uint64_t p; asm volatile("createpolicy.fractional.L2::evict_first.b64 %0, 1.0;" : "=l"(p)); return p;
}
__device__ __forceinline__ void tma_2d_mc(uint32_t dst, const CUtensorMap* m, uint32_t bar, int c0, int c1, uint64_t pol) {
  asm volatile("cp.async.bulk.tensor.2d.shared::cluster.global.mbarrier::complete_tx::bytes.multicast::cluster.L2::cache_hint [%0], [%1, {%3, %4}], [%2], %5, %6;"
               :: "r"(dst), "l"(m), "r"(bar), "r"(c0), "r"(c1), "h"((uint16_t)3), "l"(pol) : "memory");
}
__device__ __forceinline__ void tma_2d_mc_nohint(uint32_t dst, const CUtensorMap* m, uint32_t bar, int c0, int c1) {
  asm volatile("cp.async.bulk.tensor.2d.shared::cluster.global.mbarrier::complete_tx::bytes.multicast::cluster [%0], [%1, {%3, %4}], [%2], %5;"
               :: "r"(dst), "l"(m), "r"(bar), "r"(c0), "r"(c1), "h"((uint16_t)3) : "memory");
}
__device__ __forceinline__ void tma_2d(uint32_t dst, const CUtensorMap* m, uint32_t bar, int c0, int c1, uint64_t pol) {
  asm volatile("cp.async.bulk.tensor.2d.shared::cluster.global.mbarrier::complete_tx::bytes.L2::cache_hint [%0], [%1, {%3, %4}], [%2], %5;"
               :: "r"(dst), "l"(m), "r"(bar), "r"(c0), "r"(c1), "l"(pol) : "memory");
}
__device__ __forceinline__ void tma_3d(uint32_t dst, const CUtensorMap* m, uint32_t bar, int c0, int c1, int c2, uint64_t pol) {
  asm volatile("cp.async.bulk.tensor.3d.shared::cluster.global.mbarrier::complete_tx::bytes.L2::cache_hint [%0], [%1, {%3, %4, %5}], [%2], %6;"
               :: "r"(dst), "l"(m), "r"(bar), "r"(c0), "r"(c1), "r"(c2), "l"(pol) : "memory");
}
__device__ __forceinline__ void tma_store_2d(const CUtensorMap* m, uint32_t src, int c0, int c1) {
  asm volatile("cp.async.bulk.tensor.2d.global.shared::cta.bulk_group [%0, {%2, %3}], [%1];"
               :: "l"(m), "r"(src), "r"(c0), "r"(c1) : "memory");
}
__device__ __forceinline__ bool mbar_test(uint32_t bar, uint32_t parity) {
  uint32_t ok;
  asm volatile("{\n.reg .pred p;\nmbarrier.test_wait.parity.shared::cta.b64 p, [%1], %2;\nselp.u32 %0, 1, 0, p;\n}"
               : "=r"(ok) : "r"(bar), "r"(parity) : "memory");
  return ok;
}
__device__ __forceinline__ unsigned long long gtimer() { unsigned long long g; asm volatile("mov.u64 %0, %%globaltimer;" : "=l"(g)); return g; }
__device__ __forceinline__ void tick() {
}
__device__ __forceinline__ void wait_until(unsigned long long t) {
#pragma unroll 1
  for (int i = 0; i < (1 << 20); i++) { if (gtimer() >= t) break; __nanosleep(40); }
}
__device__ __forceinline__ void mbar_arrive(uint32_t bar) {
  asm volatile("mbarrier.arrive.shared::cta.b64 _, [%0];" :: "r"(bar) : "memory");
}
__device__ __forceinline__ void wg_fence()  { asm volatile("wgmma.fence.sync.aligned;" ::: "memory"); }
__device__ __forceinline__ void wg_commit() { asm volatile("wgmma.commit_group.sync.aligned;" ::: "memory"); }
template <int N> __device__ __forceinline__ void wg_wait() { asm volatile("wgmma.wait_group.sync.aligned %0;" :: "n"(N) : "memory"); }
__device__ __forceinline__ void tok_wait(int id) { if (ORDER) asm volatile("bar.sync %0, 256;" :: "r"(id) : "memory"); }
__device__ __forceinline__ void tok_pass(int id) { if (ORDER) asm volatile("bar.arrive %0, 256;" :: "r"(id) : "memory"); }
__device__ __forceinline__ void bar_sync(int id, int n)   { asm volatile("bar.sync %0, %1;" :: "r"(id), "r"(n) : "memory"); }
__device__ __forceinline__ void cluster_arrive_relaxed() { asm volatile("barrier.cluster.arrive.relaxed.aligned;" ::: "memory"); }
__device__ __forceinline__ void cluster_wait()           { asm volatile("barrier.cluster.wait.aligned;" ::: "memory"); }
__device__ __forceinline__ unsigned ld_relaxed(const unsigned* p) {
  unsigned v; asm volatile("ld.relaxed.gpu.global.u32 %0, [%1];" : "=r"(v) : "l"(p) : "memory"); return v;
}
__device__ __forceinline__ void red_release_add(unsigned* p, unsigned v) {
  asm volatile("red.release.gpu.global.add.u32 [%0], %1;" :: "l"(p), "r"(v) : "memory");
}
__device__ __forceinline__ void spin_until(const unsigned* p, unsigned target) {
  asm volatile("{\n.reg .pred P1;\n.reg .u32 cnt, v;\nmov.u32 cnt, 0;\n"
               "LAB_SPIN:\n"
               "ld.acquire.gpu.global.u32 v, [%0];\n"
               "sub.u32 v, v, %1;\n"
               "setp.ge.s32 P1, v, 0;\n"
               "@P1 bra DONE;\n"
               "nanosleep.u32 20;\n"
               "add.u32 cnt, cnt, 1;\n"
               "setp.lt.u32 P1, cnt, 4194304;\n"
               "@P1 bra LAB_SPIN;\n"
               "trap;\n"
               "DONE:\n}"
               :: "l"(p), "r"(target) : "memory");
}
__device__ __forceinline__ uint32_t desc_lo(uint32_t addr, uint32_t lbo) { return ((addr & 0x3FFFF) >> 4) | ((lbo >> 4) << 16); }
__device__ __forceinline__ uint64_t desc(uint32_t lo, uint32_t byte_off = 0, uint32_t hi = 0x40000040u) {
  uint64_t d;
  asm("mov.b64 %0, {%1, %2};" : "=l"(d) : "r"(lo + (byte_off >> 4)), "r"(hi));
  return d;
}
__device__ __forceinline__ uint32_t pack_bf16(float lo, float hi) {
  uint32_t r; asm("cvt.rn.bf16x2.f32 %0, %1, %2;" : "=r"(r) : "f"(hi), "f"(lo)); return r;
}
__device__ __forceinline__ float ex2(float x) { float r; asm("ex2.approx.ftz.f32 %0, %1;" : "=f"(r) : "f"(x)); return r; }

__device__ __forceinline__ void wgmma_ss_n192_tb1(float (&d)[96], uint64_t descA, uint64_t descB) {
  asm volatile("{\n.reg .pred p;\n"
    "setp.ne.b32 p, 1, 0;\n"
    "wgmma.mma_async.sync.aligned.m64n192k16.f32.bf16.bf16 "
    "{%0, %1, %2, %3, %4, %5, %6, %7, %8, %9, %10, %11, %12, %13, %14, %15, "
    "%16, %17, %18, %19, %20, %21, %22, %23, %24, %25, %26, %27, %28, %29, %30, %31, "
    "%32, %33, %34, %35, %36, %37, %38, %39, %40, %41, %42, %43, %44, %45, %46, %47, "
    "%48, %49, %50, %51, %52, %53, %54, %55, %56, %57, %58, %59, %60, %61, %62, %63, "
    "%64, %65, %66, %67, %68, %69, %70, %71, %72, %73, %74, %75, %76, %77, %78, %79, "
    "%80, %81, %82, %83, %84, %85, %86, %87, %88, %89, %90, %91, %92, %93, %94, %95}, "
    "%96, %97, p, 1, 1, 0, 1;\n}\n"
    : "+f"(d[0]), "+f"(d[1]), "+f"(d[2]), "+f"(d[3]), "+f"(d[4]), "+f"(d[5]), "+f"(d[6]), "+f"(d[7]),
      "+f"(d[8]), "+f"(d[9]), "+f"(d[10]), "+f"(d[11]), "+f"(d[12]), "+f"(d[13]), "+f"(d[14]), "+f"(d[15]),
      "+f"(d[16]), "+f"(d[17]), "+f"(d[18]), "+f"(d[19]), "+f"(d[20]), "+f"(d[21]), "+f"(d[22]), "+f"(d[23]),
      "+f"(d[24]), "+f"(d[25]), "+f"(d[26]), "+f"(d[27]), "+f"(d[28]), "+f"(d[29]), "+f"(d[30]), "+f"(d[31]),
      "+f"(d[32]), "+f"(d[33]), "+f"(d[34]), "+f"(d[35]), "+f"(d[36]), "+f"(d[37]), "+f"(d[38]), "+f"(d[39]),
      "+f"(d[40]), "+f"(d[41]), "+f"(d[42]), "+f"(d[43]), "+f"(d[44]), "+f"(d[45]), "+f"(d[46]), "+f"(d[47]),
      "+f"(d[48]), "+f"(d[49]), "+f"(d[50]), "+f"(d[51]), "+f"(d[52]), "+f"(d[53]), "+f"(d[54]), "+f"(d[55]),
      "+f"(d[56]), "+f"(d[57]), "+f"(d[58]), "+f"(d[59]), "+f"(d[60]), "+f"(d[61]), "+f"(d[62]), "+f"(d[63]),
      "+f"(d[64]), "+f"(d[65]), "+f"(d[66]), "+f"(d[67]), "+f"(d[68]), "+f"(d[69]), "+f"(d[70]), "+f"(d[71]),
      "+f"(d[72]), "+f"(d[73]), "+f"(d[74]), "+f"(d[75]), "+f"(d[76]), "+f"(d[77]), "+f"(d[78]), "+f"(d[79]),
      "+f"(d[80]), "+f"(d[81]), "+f"(d[82]), "+f"(d[83]), "+f"(d[84]), "+f"(d[85]), "+f"(d[86]), "+f"(d[87]),
      "+f"(d[88]), "+f"(d[89]), "+f"(d[90]), "+f"(d[91]), "+f"(d[92]), "+f"(d[93]), "+f"(d[94]), "+f"(d[95])
    : "l"(descA), "l"(descB));
}

__device__ __forceinline__ void wgmma_ss_n192_tb1_init(float (&d)[96], uint64_t descA, uint64_t descB) {
  asm volatile("{\n.reg .pred p;\n"
    "setp.ne.b32 p, 0, 0;\n"
    "wgmma.mma_async.sync.aligned.m64n192k16.f32.bf16.bf16 "
    "{%0, %1, %2, %3, %4, %5, %6, %7, %8, %9, %10, %11, %12, %13, %14, %15, "
    "%16, %17, %18, %19, %20, %21, %22, %23, %24, %25, %26, %27, %28, %29, %30, %31, "
    "%32, %33, %34, %35, %36, %37, %38, %39, %40, %41, %42, %43, %44, %45, %46, %47, "
    "%48, %49, %50, %51, %52, %53, %54, %55, %56, %57, %58, %59, %60, %61, %62, %63, "
    "%64, %65, %66, %67, %68, %69, %70, %71, %72, %73, %74, %75, %76, %77, %78, %79, "
    "%80, %81, %82, %83, %84, %85, %86, %87, %88, %89, %90, %91, %92, %93, %94, %95}, "
    "%96, %97, p, 1, 1, 0, 1;\n}\n"
    : "=f"(d[0]), "=f"(d[1]), "=f"(d[2]), "=f"(d[3]), "=f"(d[4]), "=f"(d[5]), "=f"(d[6]), "=f"(d[7]),
      "=f"(d[8]), "=f"(d[9]), "=f"(d[10]), "=f"(d[11]), "=f"(d[12]), "=f"(d[13]), "=f"(d[14]), "=f"(d[15]),
      "=f"(d[16]), "=f"(d[17]), "=f"(d[18]), "=f"(d[19]), "=f"(d[20]), "=f"(d[21]), "=f"(d[22]), "=f"(d[23]),
      "=f"(d[24]), "=f"(d[25]), "=f"(d[26]), "=f"(d[27]), "=f"(d[28]), "=f"(d[29]), "=f"(d[30]), "=f"(d[31]),
      "=f"(d[32]), "=f"(d[33]), "=f"(d[34]), "=f"(d[35]), "=f"(d[36]), "=f"(d[37]), "=f"(d[38]), "=f"(d[39]),
      "=f"(d[40]), "=f"(d[41]), "=f"(d[42]), "=f"(d[43]), "=f"(d[44]), "=f"(d[45]), "=f"(d[46]), "=f"(d[47]),
      "=f"(d[48]), "=f"(d[49]), "=f"(d[50]), "=f"(d[51]), "=f"(d[52]), "=f"(d[53]), "=f"(d[54]), "=f"(d[55]),
      "=f"(d[56]), "=f"(d[57]), "=f"(d[58]), "=f"(d[59]), "=f"(d[60]), "=f"(d[61]), "=f"(d[62]), "=f"(d[63]),
      "=f"(d[64]), "=f"(d[65]), "=f"(d[66]), "=f"(d[67]), "=f"(d[68]), "=f"(d[69]), "=f"(d[70]), "=f"(d[71]),
      "=f"(d[72]), "=f"(d[73]), "=f"(d[74]), "=f"(d[75]), "=f"(d[76]), "=f"(d[77]), "=f"(d[78]), "=f"(d[79]),
      "=f"(d[80]), "=f"(d[81]), "=f"(d[82]), "=f"(d[83]), "=f"(d[84]), "=f"(d[85]), "=f"(d[86]), "=f"(d[87]),
      "=f"(d[88]), "=f"(d[89]), "=f"(d[90]), "=f"(d[91]), "=f"(d[92]), "=f"(d[93]), "=f"(d[94]), "=f"(d[95])
    : "l"(descA), "l"(descB));
}

__device__ __forceinline__ void wgmma_ss_n160_tb1(float (&d)[80], uint64_t descA, uint64_t descB) {
  asm volatile("{\n.reg .pred p;\n"
    "setp.ne.b32 p, 1, 0;\n"
    "wgmma.mma_async.sync.aligned.m64n160k16.f32.bf16.bf16 "
    "{%0, %1, %2, %3, %4, %5, %6, %7, %8, %9, %10, %11, %12, %13, %14, %15, "
    "%16, %17, %18, %19, %20, %21, %22, %23, %24, %25, %26, %27, %28, %29, %30, %31, "
    "%32, %33, %34, %35, %36, %37, %38, %39, %40, %41, %42, %43, %44, %45, %46, %47, "
    "%48, %49, %50, %51, %52, %53, %54, %55, %56, %57, %58, %59, %60, %61, %62, %63, "
    "%64, %65, %66, %67, %68, %69, %70, %71, %72, %73, %74, %75, %76, %77, %78, %79}, "
    "%80, %81, p, 1, 1, 0, 1;\n}\n"
    : "+f"(d[0]), "+f"(d[1]), "+f"(d[2]), "+f"(d[3]), "+f"(d[4]), "+f"(d[5]), "+f"(d[6]), "+f"(d[7]),
      "+f"(d[8]), "+f"(d[9]), "+f"(d[10]), "+f"(d[11]), "+f"(d[12]), "+f"(d[13]), "+f"(d[14]), "+f"(d[15]),
      "+f"(d[16]), "+f"(d[17]), "+f"(d[18]), "+f"(d[19]), "+f"(d[20]), "+f"(d[21]), "+f"(d[22]), "+f"(d[23]),
      "+f"(d[24]), "+f"(d[25]), "+f"(d[26]), "+f"(d[27]), "+f"(d[28]), "+f"(d[29]), "+f"(d[30]), "+f"(d[31]),
      "+f"(d[32]), "+f"(d[33]), "+f"(d[34]), "+f"(d[35]), "+f"(d[36]), "+f"(d[37]), "+f"(d[38]), "+f"(d[39]),
      "+f"(d[40]), "+f"(d[41]), "+f"(d[42]), "+f"(d[43]), "+f"(d[44]), "+f"(d[45]), "+f"(d[46]), "+f"(d[47]),
      "+f"(d[48]), "+f"(d[49]), "+f"(d[50]), "+f"(d[51]), "+f"(d[52]), "+f"(d[53]), "+f"(d[54]), "+f"(d[55]),
      "+f"(d[56]), "+f"(d[57]), "+f"(d[58]), "+f"(d[59]), "+f"(d[60]), "+f"(d[61]), "+f"(d[62]), "+f"(d[63]),
      "+f"(d[64]), "+f"(d[65]), "+f"(d[66]), "+f"(d[67]), "+f"(d[68]), "+f"(d[69]), "+f"(d[70]), "+f"(d[71]),
      "+f"(d[72]), "+f"(d[73]), "+f"(d[74]), "+f"(d[75]), "+f"(d[76]), "+f"(d[77]), "+f"(d[78]), "+f"(d[79])
    : "l"(descA), "l"(descB));
}

__device__ __forceinline__ void wgmma_ss_n160_tb1_init(float (&d)[80], uint64_t descA, uint64_t descB) {
  asm volatile("{\n.reg .pred p;\n"
    "setp.ne.b32 p, 0, 0;\n"
    "wgmma.mma_async.sync.aligned.m64n160k16.f32.bf16.bf16 "
    "{%0, %1, %2, %3, %4, %5, %6, %7, %8, %9, %10, %11, %12, %13, %14, %15, "
    "%16, %17, %18, %19, %20, %21, %22, %23, %24, %25, %26, %27, %28, %29, %30, %31, "
    "%32, %33, %34, %35, %36, %37, %38, %39, %40, %41, %42, %43, %44, %45, %46, %47, "
    "%48, %49, %50, %51, %52, %53, %54, %55, %56, %57, %58, %59, %60, %61, %62, %63, "
    "%64, %65, %66, %67, %68, %69, %70, %71, %72, %73, %74, %75, %76, %77, %78, %79}, "
    "%80, %81, p, 1, 1, 0, 1;\n}\n"
    : "=f"(d[0]), "=f"(d[1]), "=f"(d[2]), "=f"(d[3]), "=f"(d[4]), "=f"(d[5]), "=f"(d[6]), "=f"(d[7]),
      "=f"(d[8]), "=f"(d[9]), "=f"(d[10]), "=f"(d[11]), "=f"(d[12]), "=f"(d[13]), "=f"(d[14]), "=f"(d[15]),
      "=f"(d[16]), "=f"(d[17]), "=f"(d[18]), "=f"(d[19]), "=f"(d[20]), "=f"(d[21]), "=f"(d[22]), "=f"(d[23]),
      "=f"(d[24]), "=f"(d[25]), "=f"(d[26]), "=f"(d[27]), "=f"(d[28]), "=f"(d[29]), "=f"(d[30]), "=f"(d[31]),
      "=f"(d[32]), "=f"(d[33]), "=f"(d[34]), "=f"(d[35]), "=f"(d[36]), "=f"(d[37]), "=f"(d[38]), "=f"(d[39]),
      "=f"(d[40]), "=f"(d[41]), "=f"(d[42]), "=f"(d[43]), "=f"(d[44]), "=f"(d[45]), "=f"(d[46]), "=f"(d[47]),
      "=f"(d[48]), "=f"(d[49]), "=f"(d[50]), "=f"(d[51]), "=f"(d[52]), "=f"(d[53]), "=f"(d[54]), "=f"(d[55]),
      "=f"(d[56]), "=f"(d[57]), "=f"(d[58]), "=f"(d[59]), "=f"(d[60]), "=f"(d[61]), "=f"(d[62]), "=f"(d[63]),
      "=f"(d[64]), "=f"(d[65]), "=f"(d[66]), "=f"(d[67]), "=f"(d[68]), "=f"(d[69]), "=f"(d[70]), "=f"(d[71]),
      "=f"(d[72]), "=f"(d[73]), "=f"(d[74]), "=f"(d[75]), "=f"(d[76]), "=f"(d[77]), "=f"(d[78]), "=f"(d[79])
    : "l"(descA), "l"(descB));
}

__device__ __forceinline__ void wgmma_rs_n96_tb0(float (&d)[48], uint32_t a0, uint32_t a1, uint32_t a2, uint32_t a3, uint64_t descB) {
  asm volatile("{\n.reg .pred p;\n"
    "setp.ne.b32 p, 1, 0;\n"
    "wgmma.mma_async.sync.aligned.m64n96k16.f32.bf16.bf16 "
    "{%0, %1, %2, %3, %4, %5, %6, %7, %8, %9, %10, %11, %12, %13, %14, %15, "
    "%16, %17, %18, %19, %20, %21, %22, %23, %24, %25, %26, %27, %28, %29, %30, %31, "
    "%32, %33, %34, %35, %36, %37, %38, %39, %40, %41, %42, %43, %44, %45, %46, %47}, "
    "{%48, %49, %50, %51}, %52, p, 1, 1, 0;\n}\n"
    : "+f"(d[0]), "+f"(d[1]), "+f"(d[2]), "+f"(d[3]), "+f"(d[4]), "+f"(d[5]), "+f"(d[6]), "+f"(d[7]),
      "+f"(d[8]), "+f"(d[9]), "+f"(d[10]), "+f"(d[11]), "+f"(d[12]), "+f"(d[13]), "+f"(d[14]), "+f"(d[15]),
      "+f"(d[16]), "+f"(d[17]), "+f"(d[18]), "+f"(d[19]), "+f"(d[20]), "+f"(d[21]), "+f"(d[22]), "+f"(d[23]),
      "+f"(d[24]), "+f"(d[25]), "+f"(d[26]), "+f"(d[27]), "+f"(d[28]), "+f"(d[29]), "+f"(d[30]), "+f"(d[31]),
      "+f"(d[32]), "+f"(d[33]), "+f"(d[34]), "+f"(d[35]), "+f"(d[36]), "+f"(d[37]), "+f"(d[38]), "+f"(d[39]),
      "+f"(d[40]), "+f"(d[41]), "+f"(d[42]), "+f"(d[43]), "+f"(d[44]), "+f"(d[45]), "+f"(d[46]), "+f"(d[47])
    : "r"(a0), "r"(a1), "r"(a2), "r"(a3), "l"(descB));
}

__device__ __forceinline__ void wgmma_rs_n96_tb0_init(float (&d)[48], uint32_t a0, uint32_t a1, uint32_t a2, uint32_t a3, uint64_t descB) {
  asm volatile("{\n.reg .pred p;\n"
    "setp.ne.b32 p, 0, 0;\n"
    "wgmma.mma_async.sync.aligned.m64n96k16.f32.bf16.bf16 "
    "{%0, %1, %2, %3, %4, %5, %6, %7, %8, %9, %10, %11, %12, %13, %14, %15, "
    "%16, %17, %18, %19, %20, %21, %22, %23, %24, %25, %26, %27, %28, %29, %30, %31, "
    "%32, %33, %34, %35, %36, %37, %38, %39, %40, %41, %42, %43, %44, %45, %46, %47}, "
    "{%48, %49, %50, %51}, %52, p, 1, 1, 0;\n}\n"
    : "=f"(d[0]), "=f"(d[1]), "=f"(d[2]), "=f"(d[3]), "=f"(d[4]), "=f"(d[5]), "=f"(d[6]), "=f"(d[7]),
      "=f"(d[8]), "=f"(d[9]), "=f"(d[10]), "=f"(d[11]), "=f"(d[12]), "=f"(d[13]), "=f"(d[14]), "=f"(d[15]),
      "=f"(d[16]), "=f"(d[17]), "=f"(d[18]), "=f"(d[19]), "=f"(d[20]), "=f"(d[21]), "=f"(d[22]), "=f"(d[23]),
      "=f"(d[24]), "=f"(d[25]), "=f"(d[26]), "=f"(d[27]), "=f"(d[28]), "=f"(d[29]), "=f"(d[30]), "=f"(d[31]),
      "=f"(d[32]), "=f"(d[33]), "=f"(d[34]), "=f"(d[35]), "=f"(d[36]), "=f"(d[37]), "=f"(d[38]), "=f"(d[39]),
      "=f"(d[40]), "=f"(d[41]), "=f"(d[42]), "=f"(d[43]), "=f"(d[44]), "=f"(d[45]), "=f"(d[46]), "=f"(d[47])
    : "r"(a0), "r"(a1), "r"(a2), "r"(a3), "l"(descB));
}

__device__ __forceinline__ void wgmma_rs_n128_tb1(float (&d)[64], uint32_t a0, uint32_t a1, uint32_t a2, uint32_t a3, uint64_t descB) {
  asm volatile("{\n.reg .pred p;\n"
    "setp.ne.b32 p, 1, 0;\n"
    "wgmma.mma_async.sync.aligned.m64n128k16.f32.bf16.bf16 "
    "{%0, %1, %2, %3, %4, %5, %6, %7, %8, %9, %10, %11, %12, %13, %14, %15, "
    "%16, %17, %18, %19, %20, %21, %22, %23, %24, %25, %26, %27, %28, %29, %30, %31, "
    "%32, %33, %34, %35, %36, %37, %38, %39, %40, %41, %42, %43, %44, %45, %46, %47, "
    "%48, %49, %50, %51, %52, %53, %54, %55, %56, %57, %58, %59, %60, %61, %62, %63}, "
    "{%64, %65, %66, %67}, %68, p, 1, 1, 1;\n}\n"
    : "+f"(d[0]), "+f"(d[1]), "+f"(d[2]), "+f"(d[3]), "+f"(d[4]), "+f"(d[5]), "+f"(d[6]), "+f"(d[7]),
      "+f"(d[8]), "+f"(d[9]), "+f"(d[10]), "+f"(d[11]), "+f"(d[12]), "+f"(d[13]), "+f"(d[14]), "+f"(d[15]),
      "+f"(d[16]), "+f"(d[17]), "+f"(d[18]), "+f"(d[19]), "+f"(d[20]), "+f"(d[21]), "+f"(d[22]), "+f"(d[23]),
      "+f"(d[24]), "+f"(d[25]), "+f"(d[26]), "+f"(d[27]), "+f"(d[28]), "+f"(d[29]), "+f"(d[30]), "+f"(d[31]),
      "+f"(d[32]), "+f"(d[33]), "+f"(d[34]), "+f"(d[35]), "+f"(d[36]), "+f"(d[37]), "+f"(d[38]), "+f"(d[39]),
      "+f"(d[40]), "+f"(d[41]), "+f"(d[42]), "+f"(d[43]), "+f"(d[44]), "+f"(d[45]), "+f"(d[46]), "+f"(d[47]),
      "+f"(d[48]), "+f"(d[49]), "+f"(d[50]), "+f"(d[51]), "+f"(d[52]), "+f"(d[53]), "+f"(d[54]), "+f"(d[55]),
      "+f"(d[56]), "+f"(d[57]), "+f"(d[58]), "+f"(d[59]), "+f"(d[60]), "+f"(d[61]), "+f"(d[62]), "+f"(d[63])
    : "r"(a0), "r"(a1), "r"(a2), "r"(a3), "l"(descB));
}

__device__ __forceinline__ void wgmma_rs_n128_tb1_init(float (&d)[64], uint32_t a0, uint32_t a1, uint32_t a2, uint32_t a3, uint64_t descB) {
  asm volatile("{\n.reg .pred p;\n"
    "setp.ne.b32 p, 0, 0;\n"
    "wgmma.mma_async.sync.aligned.m64n128k16.f32.bf16.bf16 "
    "{%0, %1, %2, %3, %4, %5, %6, %7, %8, %9, %10, %11, %12, %13, %14, %15, "
    "%16, %17, %18, %19, %20, %21, %22, %23, %24, %25, %26, %27, %28, %29, %30, %31, "
    "%32, %33, %34, %35, %36, %37, %38, %39, %40, %41, %42, %43, %44, %45, %46, %47, "
    "%48, %49, %50, %51, %52, %53, %54, %55, %56, %57, %58, %59, %60, %61, %62, %63}, "
    "{%64, %65, %66, %67}, %68, p, 1, 1, 1;\n}\n"
    : "=f"(d[0]), "=f"(d[1]), "=f"(d[2]), "=f"(d[3]), "=f"(d[4]), "=f"(d[5]), "=f"(d[6]), "=f"(d[7]),
      "=f"(d[8]), "=f"(d[9]), "=f"(d[10]), "=f"(d[11]), "=f"(d[12]), "=f"(d[13]), "=f"(d[14]), "=f"(d[15]),
      "=f"(d[16]), "=f"(d[17]), "=f"(d[18]), "=f"(d[19]), "=f"(d[20]), "=f"(d[21]), "=f"(d[22]), "=f"(d[23]),
      "=f"(d[24]), "=f"(d[25]), "=f"(d[26]), "=f"(d[27]), "=f"(d[28]), "=f"(d[29]), "=f"(d[30]), "=f"(d[31]),
      "=f"(d[32]), "=f"(d[33]), "=f"(d[34]), "=f"(d[35]), "=f"(d[36]), "=f"(d[37]), "=f"(d[38]), "=f"(d[39]),
      "=f"(d[40]), "=f"(d[41]), "=f"(d[42]), "=f"(d[43]), "=f"(d[44]), "=f"(d[45]), "=f"(d[46]), "=f"(d[47]),
      "=f"(d[48]), "=f"(d[49]), "=f"(d[50]), "=f"(d[51]), "=f"(d[52]), "=f"(d[53]), "=f"(d[54]), "=f"(d[55]),
      "=f"(d[56]), "=f"(d[57]), "=f"(d[58]), "=f"(d[59]), "=f"(d[60]), "=f"(d[61]), "=f"(d[62]), "=f"(d[63])
    : "r"(a0), "r"(a1), "r"(a2), "r"(a3), "l"(descB));
}

__device__ __forceinline__ void wgmma_rs_n64_tb1(float (&d)[32], uint32_t a0, uint32_t a1, uint32_t a2, uint32_t a3, uint64_t descB) {
  asm volatile("{\n.reg .pred p;\n"
    "setp.ne.b32 p, 1, 0;\n"
    "wgmma.mma_async.sync.aligned.m64n64k16.f32.bf16.bf16 "
    "{%0, %1, %2, %3, %4, %5, %6, %7, %8, %9, %10, %11, %12, %13, %14, %15, "
    "%16, %17, %18, %19, %20, %21, %22, %23, %24, %25, %26, %27, %28, %29, %30, %31}, "
    "{%32, %33, %34, %35}, %36, p, 1, 1, 1;\n}\n"
    : "+f"(d[0]), "+f"(d[1]), "+f"(d[2]), "+f"(d[3]), "+f"(d[4]), "+f"(d[5]), "+f"(d[6]), "+f"(d[7]),
      "+f"(d[8]), "+f"(d[9]), "+f"(d[10]), "+f"(d[11]), "+f"(d[12]), "+f"(d[13]), "+f"(d[14]), "+f"(d[15]),
      "+f"(d[16]), "+f"(d[17]), "+f"(d[18]), "+f"(d[19]), "+f"(d[20]), "+f"(d[21]), "+f"(d[22]), "+f"(d[23]),
      "+f"(d[24]), "+f"(d[25]), "+f"(d[26]), "+f"(d[27]), "+f"(d[28]), "+f"(d[29]), "+f"(d[30]), "+f"(d[31])
    : "r"(a0), "r"(a1), "r"(a2), "r"(a3), "l"(descB));
}

__device__ __forceinline__ void wgmma_rs_n64_tb1_init(float (&d)[32], uint32_t a0, uint32_t a1, uint32_t a2, uint32_t a3, uint64_t descB) {
  asm volatile("{\n.reg .pred p;\n"
    "setp.ne.b32 p, 0, 0;\n"
    "wgmma.mma_async.sync.aligned.m64n64k16.f32.bf16.bf16 "
    "{%0, %1, %2, %3, %4, %5, %6, %7, %8, %9, %10, %11, %12, %13, %14, %15, "
    "%16, %17, %18, %19, %20, %21, %22, %23, %24, %25, %26, %27, %28, %29, %30, %31}, "
    "{%32, %33, %34, %35}, %36, p, 1, 1, 1;\n}\n"
    : "=f"(d[0]), "=f"(d[1]), "=f"(d[2]), "=f"(d[3]), "=f"(d[4]), "=f"(d[5]), "=f"(d[6]), "=f"(d[7]),
      "=f"(d[8]), "=f"(d[9]), "=f"(d[10]), "=f"(d[11]), "=f"(d[12]), "=f"(d[13]), "=f"(d[14]), "=f"(d[15]),
      "=f"(d[16]), "=f"(d[17]), "=f"(d[18]), "=f"(d[19]), "=f"(d[20]), "=f"(d[21]), "=f"(d[22]), "=f"(d[23]),
      "=f"(d[24]), "=f"(d[25]), "=f"(d[26]), "=f"(d[27]), "=f"(d[28]), "=f"(d[29]), "=f"(d[30]), "=f"(d[31])
    : "r"(a0), "r"(a1), "r"(a2), "r"(a3), "l"(descB));
}

template <int V> struct Int { static constexpr int value = V; };

#define WAIT_FULL(R) do { PROF_USE_WG(1, (R).u); TR_WG(0x100 + (R).u); mbar_wait((R).full(full0), (R).phase()); TR_WG(0x200 + (R).u); PROF_USE_WG(2, (R).u); } while (0)

struct Ring {
  uint32_t u;
  __device__ __forceinline__ uint32_t slot()  const { return u & (NSLOT - 1); }
  __device__ __forceinline__ uint32_t phase() const { return (u >> 2) & 1; }
  __device__ __forceinline__ uint32_t full(uint32_t full0)   const { return full0 + 8 * slot(); }
  __device__ __forceinline__ uint32_t empty(uint32_t full0)  const { return full0 + 8 * NSLOT + 8 * slot(); }
  __device__ __forceinline__ uint32_t addr(uint32_t ring)    const { return ring + slot() * SLOT_BYTES; }
  __device__ __forceinline__ Ring operator+(uint32_t d) const { return Ring{u + d}; }
};

__device__ __forceinline__ void softmax96(float (&s)[48], uint32_t (&p)[24], float& r0, float& r1) {
  const float c = 0.07216878364870322f * 1.4426950408889634f;
  float a0[6], a1[6];
#pragma unroll
  for (int j = 0; j < 6; j++) {
    a0[j] = fmaxf(fmaxf(s[8 * j], s[8 * j + 1]), fmaxf(s[8 * j + 4], s[8 * j + 5]));
    a1[j] = fmaxf(fmaxf(s[8 * j + 2], s[8 * j + 3]), fmaxf(s[8 * j + 6], s[8 * j + 7]));
  }
  float m0 = fmaxf(fmaxf(fmaxf(a0[0], a0[1]), fmaxf(a0[2], a0[3])), fmaxf(a0[4], a0[5]));
  float m1 = fmaxf(fmaxf(fmaxf(a1[0], a1[1]), fmaxf(a1[2], a1[3])), fmaxf(a1[4], a1[5]));
  m0 = fmaxf(m0, __shfl_xor_sync(0xffffffffu, m0, 1));
  m1 = fmaxf(m1, __shfl_xor_sync(0xffffffffu, m1, 1));
  m0 = fmaxf(m0, __shfl_xor_sync(0xffffffffu, m0, 2));
  m1 = fmaxf(m1, __shfl_xor_sync(0xffffffffu, m1, 2));
  const float b0 = -m0 * c, b1 = -m1 * c;
  float l0 = 0.f, l1 = 0.f;
#pragma unroll
  for (int j = 0; j < 12; j++) {
    const float e0 = ex2(fmaf(s[4 * j],     c, b0)), e1 = ex2(fmaf(s[4 * j + 1], c, b0));
    const float e2 = ex2(fmaf(s[4 * j + 2], c, b1)), e3 = ex2(fmaf(s[4 * j + 3], c, b1));
    l0 += e0 + e1;
    l1 += e2 + e3;
    p[2 * j]     = pack_bf16(e0, e1);
    p[2 * j + 1] = pack_bf16(e2, e3);
  }
  l0 += __shfl_xor_sync(0xffffffffu, l0, 1);
  l1 += __shfl_xor_sync(0xffffffffu, l1, 1);
  l0 += __shfl_xor_sync(0xffffffffu, l0, 2);
  l1 += __shfl_xor_sync(0xffffffffu, l1, 2);
  asm("rcp.approx.ftz.f32 %0, %1;" : "=f"(r0) : "f"(l0));
  asm("rcp.approx.ftz.f32 %0, %1;" : "=f"(r1) : "f"(l1));
}

template <bool INIT>
__device__ __forceinline__ void qk_mma(float (&s)[48], const uint32_t (&qf)[48], uint32_t box0, uint32_t box1, uint32_t box2) {
  const uint32_t d0 = desc_lo(box0, 16), d1 = desc_lo(box1, 16), d2 = desc_lo(box2, 16);
  if (INIT) wgmma_rs_n96_tb0_init(s, qf[0], qf[1], qf[2], qf[3], desc(d0));
  else      wgmma_rs_n96_tb0(s, qf[0], qf[1], qf[2], qf[3], desc(d0));
#pragma unroll
  for (int k = 1; k < 12; k++)
    wgmma_rs_n96_tb0(s, qf[4 * k], qf[4 * k + 1], qf[4 * k + 2], qf[4 * k + 3], desc(k < 4 ? d0 : k < 8 ? d1 : d2, (k & 3) * 32));
}
template <bool INIT>
__device__ __forceinline__ void pv_mma(float (&o)[96], const uint32_t (&pf)[24], uint32_t box01, uint32_t box2) {
  float (&oa)[64] = *reinterpret_cast<float (*)[64]>(&o[0]);
  float (&ob)[32] = *reinterpret_cast<float (*)[32]>(&o[64]);
  const uint32_t da = desc_lo(box01, 12288), db = desc_lo(box2, 12288);
  if (INIT) { wgmma_rs_n128_tb1_init(oa, pf[0], pf[1], pf[2], pf[3], desc(da)); wgmma_rs_n64_tb1_init(ob, pf[0], pf[1], pf[2], pf[3], desc(db)); }
  else      { wgmma_rs_n128_tb1(oa, pf[0], pf[1], pf[2], pf[3], desc(da));      wgmma_rs_n64_tb1(ob, pf[0], pf[1], pf[2], pf[3], desc(db)); }
#pragma unroll
  for (int k = 1; k < 6; k++) {
    wgmma_rs_n128_tb1(oa, pf[4 * k], pf[4 * k + 1], pf[4 * k + 2], pf[4 * k + 3], desc(da, k * 2048));
    wgmma_rs_n64_tb1(ob, pf[4 * k], pf[4 * k + 1], pf[4 * k + 2], pf[4 * k + 3], desc(db, k * 2048));
  }
}

__global__ void __cluster_dims__(2, 1, 1) __launch_bounds__(NTHREADS, 1)
fused_attn_kernel(const __grid_constant__ Params prm, __nv_bfloat16* __restrict__ out) {
  extern __shared__ uint8_t smem_raw[];
  __shared__ uint64_t s_bars[2 * NSLOT + 10];
  __shared__ uint32_t s_dummy[64];
  __shared__ volatile uint32_t s_prog;

  const uint32_t ring = (smem_u32(smem_raw) + 1023) & ~1023u;
  const uint32_t stg  = ring + NSLOT * SLOT_BYTES;
  const uint32_t full0 = smem_u32(&s_bars[0]);
  const uint32_t o_done  = full0 + 16 * NSLOT;
  const uint32_t o_ready = o_done + 48;

  const int tid = threadIdx.x, lane = tid & 31;
  const int warp = __shfl_sync(0xffffffffu, tid >> 5, 0);
  const int rank = blockIdx.x & 1, cl = c_cluster_map[blockIdx.x >> 1], cta = 2 * cl + rank;
  const int grp = cl >> 3, prob = grp >> 2, bp = grp & 3, j8 = cl & 7;
  const int split = j8 >> 1;

  if (tid == 12 * 32) {
#pragma unroll
    for (int s = 0; s < NSLOT; s++) { mbar_init(full0 + 8 * s, 1); mbar_init(full0 + 8 * NSLOT + 8 * s, 6); }
    for (int s = 0; s < 6; s++) mbar_init(o_done + 8 * s, 12);
    for (int s = 0; s < 4; s++) mbar_init(o_ready + 8 * s, 1);
    s_prog = NSLOT;
    asm volatile("fence.mbarrier_init.release.cluster;" ::: "memory");
  }
  __syncthreads();
  cluster_arrive_relaxed();
  if (tid == 12 * 32) {
    const int h = 2 * j8 + rank;
    const uint64_t pol = POL_STREAM();
#pragma unroll
    for (int s = 0; s < NSLOT; s++) {
      mbar_expect_tx(full0 + 8 * s, SLOT_BYTES);
      tma_3d(ring + s * SLOT_BYTES + B_OFF, &prm.wq[prob], full0 + 8 * s, 0, 64 * s, 3 * h, pol);
    }
  }
  __syncwarp();
  cluster_wait();
  if (tid == 12 * 32) {
#pragma unroll
    for (int s = 0; s < NSLOT; s++)
      tma_2d_mc_nohint(ring + s * SLOT_BYTES + rank * 12288, &prm.x[prob], full0 + 8 * s, 64 * s, 192 * bp + 96 * rank);
  }

  if (warp >= 12) {
    asm volatile("setmaxnreg.dec.sync.aligned.u32 32;");
    if (warp == 12) {
      if (lane == 0) {
        Ring r{0};
        const uint64_t pol_s = POL_STREAM();
        const int ncol0 = 320 * (j8 & 1);
        TR_DECL;
        PROF(3, 1);
#pragma unroll 1
        for (int w = 0; w < 2; w++) {
          const int h = 16 * w + 2 * j8 + rank;
#pragma unroll 1
          for (int ks = 0; ks < 10; ks++) {
            const uint32_t fb = r.full(full0), sl = r.addr(ring);
            if (r.u >= NSLOT) {
              mbar_wait(r.empty(full0), r.phase() ^ 1);
              mbar_expect_tx(fb, SLOT_BYTES);
              PROF_USE(0, r.u);
              TR(3, 0x400 + r.u);
              s_prog = r.u;
              tick();
              tma_3d(sl + B_OFF, &prm.wq[prob], fb, 0, 64 * ks, 3 * h, pol_s);
              tma_2d_mc_nohint(sl + rank * 12288, &prm.x[prob], fb, 64 * ks, 192 * bp + 96 * rank);
            }
            r.u++;
          }
          PROF(3, 2 + 2 * w);
#pragma unroll 1
          for (int t = 0; t < 3; t++) {
            const uint32_t fb = r.full(full0), sl = r.addr(ring);
            const int row0 = ((2 * bp) * 32 + h) * 96, row1 = row0 + 32 * 96;
            mbar_wait(r.empty(full0), r.phase() ^ 1);
            mbar_expect_tx(fb, SLOT_BYTES);
            PROF_USE(0, r.u);
            TR(3, 0x400 + r.u);
            s_prog = r.u;
            if (t == 0) {
              tma_3d(sl,         &prm.k[prob],  fb, 0, row0, 0, pol_s);
              tma_3d(sl + 36864, &prm.k1[prob], fb, 0, row1, 0, pol_s);
            } else if (t == 1) {
              tma_3d(sl,         &prm.k1[prob], fb, 0, row1, 1, pol_s);
              tma_3d(sl + 12288, &prm.k1[prob], fb, 0, row1, 2, pol_s);
              tma_3d(sl + 24576, &prm.v1[prob], fb, 0, row0, 0, pol_s);
              tma_3d(sl + 36864, &prm.v1[prob], fb, 0, row0, 1, pol_s);
            } else {
              tma_3d(sl,         &prm.v1[prob], fb, 0, row0, 2, pol_s);
              tma_3d(sl + 12288, &prm.v[prob],  fb, 0, row1, 0, pol_s);
            }
            r.u++;
          }
          PROF(3, 3 + 2 * w);
        }
#pragma unroll 1
        for (int i = 0; i < 24; i++) {
          const int h = i < 12 ? 4 * split + i / 3 : 16 + 4 * split + (i & 3);
          const int c = i < 12 ? i % 3 : (i - 12) >> 2;
          const uint32_t fb = r.full(full0), sl = r.addr(ring);
          const int k0 = h * 192 + c * 64;
          mbar_wait(r.empty(full0), r.phase() ^ 1);
          mbar_expect_tx(fb, SLOT_BYTES);
          PROF_USE(0, r.u);
          TR(3, 0x400 + r.u);
          s_prog = r.u;
          tick();
          tma_2d(sl + B_OFF,         &prm.wo[prob],   fb, ncol0 + 192 * rank,      k0, pol_s);
          tma_2d(sl + B_OFF + 8192,  &prm.wo[prob],   fb, ncol0 + 192 * rank + 64, k0, pol_s);
          tma_2d(sl + B_OFF + 16384, &prm.wo[prob],   fb, ncol0 + 128, k0, pol_s);
          if (i == 0 || (i >= 12 && (i & 3) == 0)) {
            mbar_wait(o_ready + 8 * (i == 0 ? 0 : (i >> 2) - 2), 0);
            if (i == 0) PROF(3, 6);
            if (i == 12) PROF(3, 7);
          }
          tma_2d_mc(sl + rank * 12288, &prm.o_ld, fb, k0, prob * 768 + 192 * bp + 96 * rank, pol_s);
          r.u++;
        }
        PROF(3, 8);
      }
    } else if (warp == 13) {
      {
        const unsigned obase = 3u * ld_relaxed(&g_epoch[cta]);
        uint32_t pub = 0, wat = 0;
#pragma unroll 1
        for (int it = 0; it < (1 << 22) && (pub < 6 || wat < 4); it++) {
          if (pub < 6 && mbar_test(o_done + 8 * pub, 0)) {
            uint32_t n = 1;
            while ((pub + n) % 3 != 0 && mbar_test(o_done + 8 * (pub + n), 0)) n++;
            if (lane == 0) {
              if (pub == 0 || pub == 3) PROF(3, 9 + 2 * (pub / 3));
              red_release_add(&g_ready[grp * 32 + 16 * (pub >= 3) + 2 * j8 + rank], n);
              if (pub == 0 || pub == 3) PROF(3, 10 + 2 * (pub / 3));
            }
            __syncwarp();
            pub += n;
          } else if (wat < 4 && pub > wat + 2) {
            const unsigned tgt = obase + (wat == 0 ? 3u : wat);
            const unsigned a = ld_relaxed(&g_ready[grp * 32 + (wat == 0 ? 0 : 16) + 4 * split + (lane & 3)]);
            if (__all_sync(0xffffffffu, (int)(a - tgt) >= 0)) {
              if (lane == 0) {
                asm volatile("fence.acq_rel.gpu;" ::: "memory");
                asm volatile("fence.proxy.async;" ::: "memory");
                mbar_arrive(o_ready + 8 * wat);
                if (wat < 2) PROF(3, 13 + wat);
              }
              __syncwarp();
              wat++;
            }
          } else {
            __nanosleep(40);
          }
        }
      }
    } else {
      {
        const int h0 = 2 * j8 + rank;
        const uint8_t* xp  = prm.xptr[prob];
        const uint8_t* wqp = prm.wqptr[prob];
        const uint8_t* wop = prm.woptr[prob];
        auto addr_of = [&](int n) -> const uint8_t* {
          if (n < 3) {
            const int i = min(n * 32 + lane, 71);
            return xp + (size_t)(192 * bp + 12 * h0 + i % 12) * 1280 + (NSLOT + i / 12) * 128;
          }
          if (n < 12 || (n >= 48 && n < 63)) {
            const bool second = n >= 48;
            const int i = (second ? n - 48 : n - 3 + 6) * 32 + lane;
            const int ks = i / 48, rem = i - ks * 48;
            return wqp + (size_t)(64 * ks + 16 * bp + rem / 3) * 12288 + (h0 + (second ? 16 : 0)) * 384 + (rem % 3) * 128;
          }
          if (n < 99) {
            const bool second = n >= 63;
            const int m = second ? n - 63 : n - 12, tile = m / 9;
            const uint8_t* base = (tile < 2) ? prm.kptr[prob] : prm.vptr[prob];
            return base + (size_t)((2 * bp + (tile & 1)) * 32 + h0 + (second ? 16 : 0)) * KV_BYTES + (m - 9 * tile) * 4096 + lane * 128;
          }
          const int i = min((n - 99) * 32 + lane, 959), hh = i / 120, rem = i - hh * 120;
          const int h = (hh >> 2) * 16 + 4 * split + (hh & 3);
          return wop + (size_t)(h * 192 + 12 * (4 * bp + 2 * (j8 & 1) + rank) + rem / 10) * 1280 + (rem % 10) * 128;
        };
        auto use_of = [&](int n) -> int {
          if (n < 3)  return NSLOT + (n * 32) / 12;
          if (n < 12) return ((n + 3) * 32) / 48;
          if (n < 48) { const int t = (n - 12) / 9; return 10 + (t < 2 ? 0 : t - 1); }
          if (n < 63) return 13 + ((n - 48) * 32) / 48;
          if (n < 99) { const int t = (n - 63) / 9; return 23 + (t < 2 ? 0 : t - 1); }
          const int hh = ((n - 99) * 32) / 120;
          const int c = (12 * (4 * bp + 2 * (j8 & 1) + rank)) >> 6;
          return hh < 4 ? 26 + 3 * hh + c : 38 + 4 * c + (hh - 4);
        };
        auto release_of = [&](int n) -> int {
          if (n < 12) return 0;
          if (n < 48) return PF_R0 + ((n - 12) * (PF_R1 - PF_R0)) / 36;
          if (n < 63) return PF_R1 + ((n - 48) * (PF_R2 - PF_R1)) / 15;
          if (n < 99) return PF_R2 + ((n - 63) * (PF_R3 - PF_R2)) / 36;
          return PF_R3 + ((n - 99) * (PF_R4 - PF_R3)) / 30;
        };
        wait_until(gtimer() + PF_DELAY_NS);
        const uint32_t dummy = smem_u32(&s_dummy[tid & 63]);
#pragma unroll 1
        for (int n = warp - 14; n < 129; n += 2) {
          const int u = use_of(n), rel = release_of(n);
          int guard = 0;
          while ((int)s_prog < rel && ++guard < (1 << 20)) __nanosleep(100);
          if (n >= 99 + PF_WO_N) break;
          if ((int)s_prog < u)
            asm volatile("cp.async.ca.shared.global.L2::128B [%0], [%1], 4;" :: "r"(dummy), "l"(addr_of(n)) : "memory");
          asm volatile("cp.async.commit_group;" ::: "memory");
          asm volatile("cp.async.wait_group %0;" :: "n"(PF_WIN) : "memory");
        }
        asm volatile("cp.async.wait_group 0;" ::: "memory");
      }
    }
  } else {
    asm volatile("setmaxnreg.inc.sync.aligned.u32 160;");
    const int wg = warp >> 2, wq4 = warp & 3;
    const bool elected = (tid & 127) == 0;
    const uint32_t descA0 = desc_lo(ring + wg * 8192, 16), descB0 = desc_lo(ring + B_OFF, 8192);
    Ring r{0};
    TR_DECL;
    TR_WG(1);
    PROF_WG(0);
    uint32_t pend[32];
    const uint32_t wstg = stg + warp * 2048;
    auto stg_acquire = [&]() {
      if (lane == 0) asm volatile("cp.async.bulk.wait_group.read 0;" ::: "memory");
      __syncwarp();
    };
    auto stage_in = [&](const uint32_t* v) {
      stg_acquire();
      const int r8 = lane & 7;
      const uint32_t st_base = wstg + (((lane >> 3) & 1) * 8 + r8) * 128;
#pragma unroll
      for (int jj = 0; jj < 4; jj++) {
        const uint32_t addr = st_base + (((2 * jj + (lane >> 4)) ^ r8) << 4);
        asm volatile("stmatrix.sync.aligned.m8n8.x4.shared.b16 [%0], {%1, %2, %3, %4};"
                     :: "r"(addr), "r"(v[4 * jj]), "r"(v[4 * jj + 1]), "r"(v[4 * jj + 2]), "r"(v[4 * jj + 3]) : "memory");
      }
    };
    auto send = [&](int wv, int box) {
      asm volatile("fence.proxy.async.shared::cta;" ::: "memory");
      __syncwarp();
      if (lane == 0) {
        tma_store_2d(&prm.o_st, wstg, (16 * wv + 2 * j8 + rank) * 192 + 64 * box, prob * 768 + 192 * bp + 16 * warp);
        asm volatile("cp.async.bulk.commit_group;" ::: "memory");
      }
    };
    auto landed = [&](int ev, auto pending) {
      if (lane == 0) {
        asm volatile("cp.async.bulk.wait_group %0;" :: "n"(decltype(pending)::value) : "memory");
        mbar_arrive(o_done + 8 * ev);
      }
    };

#pragma unroll 1
    for (int w = 0; w < 2; w++) {
      uint32_t qf[48];
      {
        float acc[96];
        {
          const uint32_t da = descA0 + r.slot() * (SLOT_BYTES >> 4), db = descB0 + r.slot() * (SLOT_BYTES >> 4);
          WAIT_FULL(r);
          if (w == 0) PROF_WG(1);
          if (w > 0) { if (wg == 0) tok_wait(14); else if (wg == 2) tok_wait(15); }
          wg_fence();
          wgmma_ss_n192_tb1_init(acc, desc(da), desc(db));
#pragma unroll
          for (int k = 1; k < 4; k++) wgmma_ss_n192_tb1(acc, desc(da, k * 32), desc(db, k * 2048));
          wg_commit();
          if (w > 0 && wg == 0) tok_pass(15);
          if (w > 0) send(0, 0);
          r.u++;
        }
#pragma unroll 1
        for (int ks = 1; ks < 10; ks++) {
          const uint32_t da = descA0 + r.slot() * (SLOT_BYTES >> 4), db = descB0 + r.slot() * (SLOT_BYTES >> 4);
          WAIT_FULL(r);
          if (ks == 9) { if (wg == 0) tok_wait(4); else if (wg == 2) tok_wait(5); }
          wg_fence();
          wgmma_ss_n192_tb1(acc, desc(da), desc(db));
          wg_commit();
          wg_wait<1>();
          TR_WG(0x300 + r.u - 1);
          if (elected) mbar_arrive_both(Ring{r.u - 1}.empty(full0));
#pragma unroll
          for (int k = 1; k < 4; k++) wgmma_ss_n192_tb1(acc, desc(da, k * 32), desc(db, k * 2048));
          wg_commit();
          if (ks == 9) tok_pass(wg == 1 ? 4 : wg == 0 ? 5 : 6);
          if (w > 0) {
            const int kk = wg == 1 ? ks - FL_LAG : ks;
            if (kk == FL_B1)      { stage_in(pend);      send(0, 1); }
            else if (kk == FL_B2) { stage_in(pend + 16); send(0, 2); }
            else if (kk == FL_LD) { landed(0, Int<0>{}); landed(1, Int<0>{}); landed(2, Int<0>{}); }
          }
          r.u++;
        }
        wg_wait<0>();
        if (elected) mbar_arrive_both(Ring{r.u - 1}.empty(full0));
        stg_acquire();
#pragma unroll
        for (int i = 0; i < 4; i++)
          asm volatile("st.shared.v4.u32 [%0], {%1, %2, %3, %4};"
                       :: "r"(wstg + i * 512 + lane * 16),
                          "r"(pack_bf16(acc[64 + 8 * i], acc[65 + 8 * i])), "r"(pack_bf16(acc[66 + 8 * i], acc[67 + 8 * i])),
                          "r"(pack_bf16(acc[68 + 8 * i], acc[69 + 8 * i])), "r"(pack_bf16(acc[70 + 8 * i], acc[71 + 8 * i])) : "memory");
#pragma unroll
        for (int i = 0; i < 32; i++) qf[i] = pack_bf16(acc[2 * i], acc[2 * i + 1]);
        asm volatile("" ::: "memory");
#pragma unroll
        for (int i = 0; i < 4; i++)
          asm volatile("ld.shared.v4.u32 {%0, %1, %2, %3}, [%4];"
                       : "=r"(qf[32 + 4 * i]), "=r"(qf[33 + 4 * i]), "=r"(qf[34 + 4 * i]), "=r"(qf[35 + 4 * i])
                       : "r"(wstg + i * 512 + lane * 16) : "memory");
      }
      PROF_WG(2 + 5 * w);
      TR_WG(2);
      const Ring rX = r, rY = r + 1, rZ = r + 2;
      r.u += 3;
      uint32_t pf[24];
      float rinv0, rinv1;
      const uint32_t aX = rX.addr(ring), aY = rY.addr(ring), aZ = rZ.addr(ring);
      {
        float s[48];
        WAIT_FULL(rX);
        if (wg == 2) WAIT_FULL(rY);
        tok_wait(wg == 1 ? 6 : wg == 0 ? 7 : 9);
        wg_fence();
        qk_mma<true>(s, qf, wg == 2 ? aX + 36864 : aX, wg == 2 ? aY : aX + 12288, wg == 2 ? aY + 12288 : aX + 24576);
        wg_commit();
        tok_pass(wg == 1 ? 7 : wg == 0 ? 8 : 10);
        wg_wait<0>();
        if (wg == 1) {
          if (wq4 < 2) {
#pragma unroll
            for (int i = 0; i < 48; i++) qf[i] = 0u;
          } else {
#pragma unroll
            for (int i = 0; i < 48; i++) s[i] = 0.f;
          }
          WAIT_FULL(rY);
          tok_wait(8);
          wg_fence();
          qk_mma<false>(s, qf, aX + 36864, aY, aY + 12288);
          wg_commit();
          tok_pass(9);
          wg_wait<0>();
        }
        if (elected) { mbar_arrive_both(rX.empty(full0)); if (wg == 2) mbar_arrive_both(rY.empty(full0)); }
        __syncwarp();
        PROF_WG(3 + 5 * w);
        TR_WG(3);
        softmax96(s, pf, rinv0, rinv1);
      }
      PROF_WG(4 + 5 * w);
      TR_WG(4);
      float o[96];
      {
        if (wg == 0) WAIT_FULL(rY);
        WAIT_FULL(rZ);
        tok_wait(wg == 0 ? 10 : wg == 1 ? 11 : 12);
        wg_fence();
        pv_mma<true>(o, pf, wg == 2 ? aZ + 12288 : aY + 24576, wg == 2 ? aZ + 36864 : aZ);
        wg_commit();
        tok_pass(wg == 0 ? 11 : wg == 1 ? 12 : 13);
        wg_wait<0>();
        if (wg == 1) {
          if (elected) mbar_arrive_both(rY.empty(full0));
          if (wq4 < 2) {
#pragma unroll
            for (int i = 0; i < 24; i++) pf[i] = 0u;
          } else {
#pragma unroll
            for (int i = 0; i < 96; i++) o[i] = 0.f;
          }
          tok_wait(13);
          wg_fence();
          pv_mma<false>(o, pf, aZ + 12288, aZ + 36864);
          wg_commit();
          tok_pass(14);
          wg_wait<0>();
        }
        if (elected) { if (wg == 0) mbar_arrive_both(rY.empty(full0)); mbar_arrive_both(rZ.empty(full0)); }
      }
      PROF_WG(5 + 5 * w);
      TR_WG(5);
      {
        uint32_t v[16];
#pragma unroll
        for (int i = 0; i < 16; i++) { const float ri = (i & 1) ? rinv1 : rinv0; v[i] = pack_bf16(o[2 * i] * ri, o[2 * i + 1] * ri); }
#pragma unroll
        for (int i = 0; i < 32; i++) { const float ri = (i & 1) ? rinv1 : rinv0; pend[i] = pack_bf16(o[32 + 2 * i] * ri, o[33 + 2 * i] * ri); }
        stage_in(v);
      }
      PROF_WG(6 + 5 * w);
      TR_WG(6);
    }

    const unsigned otarget = ld_relaxed(&g_epoch[cta]) + 1u, target = 3u * otarget;
    const uint32_t bhi = 0x40000040u | (rank ? 4u << 17 : 0u);
    float acc[80];
    {
      {
        const uint32_t da = descA0 + r.slot() * (SLOT_BYTES >> 4), db = descB0 + r.slot() * (SLOT_BYTES >> 4);
        WAIT_FULL(r);
        PROF_WG(12);
        if (wg == 0) tok_wait(14); else if (wg == 2) tok_wait(15);
        wg_fence();
        wgmma_ss_n160_tb1_init(acc, desc(da), desc(db, 0, bhi));
#pragma unroll
        for (int k = 1; k < 4; k++) wgmma_ss_n160_tb1(acc, desc(da, k * 32), desc(db, k * 2048, bhi));
        wg_commit();
        if (wg == 0) tok_pass(15);
        send(1, 0);
        r.u++;
      }
#pragma unroll 1
      for (int ks = 1; ks < 24; ks++) {
        const uint32_t da = descA0 + r.slot() * (SLOT_BYTES >> 4), db = descB0 + r.slot() * (SLOT_BYTES >> 4);
        WAIT_FULL(r);
        wg_fence();
        wgmma_ss_n160_tb1(acc, desc(da), desc(db, 0, bhi));
        wg_commit();
        wg_wait<1>();
        TR_WG(0x300 + r.u - 1);
        if (elected) mbar_arrive_both(Ring{r.u - 1}.empty(full0));
#pragma unroll
        for (int k = 1; k < 4; k++) wgmma_ss_n160_tb1(acc, desc(da, k * 32), desc(db, k * 2048, bhi));
        wg_commit();
        {
          const int kk = wg == 1 ? ks - FL2_LAG : ks;
          if (kk == FL2_B1)      { landed(3, Int<0>{}); stage_in(pend);      send(1, 1); }
          else if (kk == FL2_B2) { landed(4, Int<0>{}); stage_in(pend + 16); send(1, 2); }
          else if (kk == FL2_LD) { landed(5, Int<0>{}); }
        }
        r.u++;
      }
      wg_wait<0>();
      if (elected) mbar_arrive_both(Ring{r.u - 1}.empty(full0));
    }
    PROF_WG(13);
    TR_WG(13);
    {
      const int t = tid;
#pragma unroll
      for (int q = 0; q < 4; q++) {
        if (q != split) {
          const int dcta = (grp * 8 + 2 * q + (j8 & 1)) * 2 + rank;
          const int srcslot = split < q ? split : split - 1;
          uint8_t* dst = g_part + (size_t)(dcta * 3 + srcslot) * PART_BYTES;
          uint32_t v[10];
#pragma unroll
          for (int i = 0; i < 10; i++) v[i] = pack_bf16(acc[20 * q + 2 * i], acc[20 * q + 2 * i + 1]);
          __stcg(reinterpret_cast<uint4*>(dst) + t,              make_uint4(v[0], v[1], v[2], v[3]));
          __stcg(reinterpret_cast<uint4*>(dst + 384 * 16) + t,   make_uint4(v[4], v[5], v[6], v[7]));
          __stcg(reinterpret_cast<uint2*>(dst + 384 * 32) + t,   make_uint2(v[8], v[9]));
        }
      }
      bar_sync(1 + wg, 128);
      if ((tid & 127) < 4 && (tid & 127) != split) {
        const int q = tid & 127;
        const int dcta = (grp * 8 + 2 * q + (j8 & 1)) * 2 + rank;
        red_release_add(&g_xflag[dcta * 3 + wg], 1u);
      }
      PROF_WG(14);
      TR_WG(14);
      float own[20];
#pragma unroll
      for (int i = 0; i < 20; i++)
        own[i] = split == 0 ? acc[i] : split == 1 ? acc[20 + i] : split == 2 ? acc[40 + i] : acc[60 + i];
      if (elected) spin_until(&g_xflag[cta * 3 + wg], target);
      bar_sync(1 + wg, 128);
      {
        uint4 a[3], c[3]; uint2 e[3];
#pragma unroll
        for (int sidx = 0; sidx < 3; sidx++) {
          const uint8_t* src = g_part + (size_t)(cta * 3 + sidx) * PART_BYTES;
          a[sidx] = __ldcg(reinterpret_cast<const uint4*>(src) + t);
          c[sidx] = __ldcg(reinterpret_cast<const uint4*>(src + 384 * 16) + t);
          e[sidx] = __ldcg(reinterpret_cast<const uint2*>(src + 384 * 32) + t);
        }
#pragma unroll
        for (int sidx = 0; sidx < 3; sidx++) {
          const uint32_t v[10] = {a[sidx].x, a[sidx].y, a[sidx].z, a[sidx].w, c[sidx].x, c[sidx].y, c[sidx].z, c[sidx].w, e[sidx].x, e[sidx].y};
#pragma unroll
          for (int i = 0; i < 10; i++) {
            own[2 * i]     += __uint_as_float(v[i] << 16);
            own[2 * i + 1] += __uint_as_float(v[i] & 0xffff0000u);
          }
        }
      }
      const int row = 192 * bp + 64 * wg + 16 * wq4 + (lane >> 2);
      __nv_bfloat16* op = out + (size_t)row * 1280 + 640 * prob + 320 * (j8 & 1) + 2 * (lane & 3);
#pragma unroll
      for (int i = 0; i < 5; i++) {
        const int a = 40 * split + 8 * i;
        const int col = rank == 0 ? a : (a < 128 ? 192 + (a ^ 32) : 32 + a);
        *reinterpret_cast<uint32_t*>(op + col)            = pack_bf16(own[4 * i],     own[4 * i + 1]);
        *reinterpret_cast<uint32_t*>(op + 8 * 1280 + col) = pack_bf16(own[4 * i + 2], own[4 * i + 3]);
      }
      if (tid == 0) g_epoch[cta] = otarget;
    }
  }
  __syncthreads();
  cluster_arrive_relaxed();
  cluster_wait();
}

typedef CUresult (*EncodeFn)(CUtensorMap*, CUtensorMapDataType, cuuint32_t, void*, const cuuint64_t*, const cuuint64_t*,
                             const cuuint32_t*, const cuuint32_t*, CUtensorMapInterleave, CUtensorMapSwizzle,
                             CUtensorMapL2promotion, CUtensorMapFloatOOBfill);

void make_map(EncodeFn enc, CUtensorMap* m, const void* ptr, int rank, const uint64_t* dims, const uint64_t* strides,
              const uint32_t* box) {
  cuuint64_t d[3], s[2]; cuuint32_t b[3], e[3] = {1, 1, 1};
  for (int i = 0; i < rank; i++) { d[i] = dims[i]; b[i] = box[i]; }
  for (int i = 0; i + 1 < rank; i++) s[i] = strides[i];
  enc(m, CU_TENSOR_MAP_DATA_TYPE_BFLOAT16, rank, const_cast<void*>(ptr), d, s, b, e, CU_TENSOR_MAP_INTERLEAVE_NONE,
      CU_TENSOR_MAP_SWIZZLE_128B, CU_TENSOR_MAP_L2_PROMOTION_L2_128B, CU_TENSOR_MAP_FLOAT_OOB_FILL_NONE);
}

}

extern "C" void kernel_launch(void* const* d_in, const int* in_sizes, int n_in, void* d_out, int out_size) {
  (void)in_sizes; (void)n_in; (void)out_size;
  static EncodeFn enc = nullptr;
  static void* o_ptr = nullptr;
  if (!enc) {
    void* fn = nullptr; cudaDriverEntryPointQueryResult st;
    cudaGetDriverEntryPoint("cuTensorMapEncodeTiled", &fn, cudaEnableDefault, &st);
    enc = (EncodeFn)fn;
    cudaGetSymbolAddress(&o_ptr, g_O);
    cudaFuncSetAttribute(fused_attn_kernel, cudaFuncAttributeMaxDynamicSharedMemorySize, SMEM_BYTES);
  }
  Params prm;
  for (int p = 0; p < 2; p++) {
    const void* x = d_in[5 * p + 0]; const void* k = d_in[5 * p + 1]; const void* v = d_in[5 * p + 2];
    const void* wq = d_in[5 * p + 3]; const void* wo = d_in[5 * p + 4];
    { uint64_t d[2] = {640, 768}, s[1] = {1280};              uint32_t b[2] = {64, 96};    make_map(enc, &prm.x[p],  x,  2, d, s, b); }
    { uint64_t d[3] = {64, 640, 96}, s[2] = {12288, 128};     uint32_t b[3] = {64, 64, 3}; make_map(enc, &prm.wq[p], wq, 3, d, s, b); }
    { uint64_t d[3] = {64, 24576, 3}, s[2] = {384, 128};      uint32_t b[3] = {64, 96, 3}; make_map(enc, &prm.k[p],  k,  3, d, s, b); }
    { uint64_t d[3] = {64, 24576, 3}, s[2] = {384, 128};      uint32_t b[3] = {64, 96, 1}; make_map(enc, &prm.k1[p], k,  3, d, s, b); }
    { uint64_t d[3] = {64, 24576, 3}, s[2] = {384, 128};      uint32_t b[3] = {64, 96, 3}; make_map(enc, &prm.v[p],  v,  3, d, s, b); }
    { uint64_t d[3] = {64, 24576, 3}, s[2] = {384, 128};      uint32_t b[3] = {64, 96, 1}; make_map(enc, &prm.v1[p], v,  3, d, s, b); }
    prm.kptr[p] = (const uint8_t*)k; prm.vptr[p] = (const uint8_t*)v;
    prm.xptr[p] = (const uint8_t*)x; prm.wqptr[p] = (const uint8_t*)wq; prm.woptr[p] = (const uint8_t*)wo;
    { uint64_t d[2] = {640, 6144}, s[1] = {1280};             uint32_t b[2] = {64, 64};    make_map(enc, &prm.wo[p], wo, 2, d, s, b); }
  }
  { uint64_t d[2] = {6144, 1536}, s[1] = {12288};        uint32_t b[2] = {64, 16};    make_map(enc, &prm.o_st, o_ptr, 2, d, s, b); }
  { uint64_t d[2] = {6144, 1536}, s[1] = {12288};        uint32_t b[2] = {64, 96};    make_map(enc, &prm.o_ld, o_ptr, 2, d, s, b); }
  fused_attn_kernel<<<128, NTHREADS, SMEM_BYTES>>>(prm, (__nv_bfloat16*)d_out);
}
```

```cpp
#include <cuda_runtime.h>
#include <cuda_bf16.h>
#include <cuda.h>
#include <stdint.h>

namespace {

#define POL_STREAM policy_evict_first
#define USE_MAP 1
#define FL_LAG 0
#define FL_B1 2
#define FL_B2 4
#define FL_LD 6
#define FL2_LAG 0
#define FL2_B1 3
#define FL2_B2 6
#define FL2_LD 9
#define TOK_S 11
#define TOK_P 5
#define TAIL_L 3
#define ORDER 1
#define PF_SKIP 0
#define PF_WO_N 0
#define ISSUE_Q 0
#define PF_MODE 1
#define PF_WIN 10
#define PF_R0 0
#define PF_R1 8
#define PF_R2 11
#define PF_R3 21
#define PF_R4 34
#define PF_DELAY_NS 0
constexpr int NTHREADS   = 512;
constexpr int NSLOT      = 4;
constexpr int SLOT_BYTES = 49152;
constexpr int B_OFF      = 24576;
constexpr int KV_BYTES   = 36864;
constexpr int STG_BYTES  = 3 * 8192;
constexpr int SMEM_BYTES = NSLOT * SLOT_BYTES + STG_BYTES + 1024  ;

struct Params {
  CUtensorMap x[2], x1[2], wq[2], k[2], k1[2], v[2], v1[2], wo[2];
  CUtensorMap o_st, o_ld;
  const uint8_t* kptr[2];
  const uint8_t* vptr[2];
  const uint8_t* xptr[2];
  const uint8_t* wqptr[2];
  const uint8_t* woptr[2];
};

__constant__ uint8_t c_cluster_map[64] = {0, 8, 16, 24, 1, 2, 4, 32, 34, 36, 6, 38, 9, 10, 12, 40, 42, 44, 14, 46, 17, 18, 20, 48, 50, 52, 22, 54, 25, 26, 28, 56, 58, 60, 30, 62, 3, 5, 33, 35, 37, 7, 39, 11, 13, 41, 43, 45, 15, 47, 19, 21, 49, 51, 53, 23, 55, 27, 29, 57, 59, 61, 31, 63};

__device__ __nv_bfloat16 g_O[1536 * 6144];
__device__ uint4         g_part[128 * 3 * 3 * 384];
__device__ unsigned      g_ready[8 * 32];
__device__ unsigned      g_xflag[128 * 3];
__device__ unsigned      g_epoch[128];

#define TR_DECL
#define TR(role, tag)
#define TR_WG(tag)
#define PROF(role, ev)
#define PROF_WG(ev)
#define PROF_USE(kind, u)
#define PROF_USE_WG(kind, u)

__device__ __forceinline__ uint32_t smem_u32(const void* p) { return (uint32_t)__cvta_generic_to_shared(p); }
__device__ __forceinline__ void mbar_init(uint32_t bar, uint32_t count) {
  asm volatile("mbarrier.init.shared::cta.b64 [%0], %1;" :: "r"(bar), "r"(count) : "memory");
}
__device__ __forceinline__ void mbar_expect_tx(uint32_t bar, uint32_t bytes) {
  asm volatile("mbarrier.arrive.expect_tx.shared::cta.b64 _, [%0], %1;" :: "r"(bar), "r"(bytes) : "memory");
}
__device__ __forceinline__ void mbar_arrive_both(uint32_t bar) {
  asm volatile("{\n.reg .b32 r0, r1;\n"
               "mapa.shared::cluster.u32 r0, %0, 0;\n"
               "mapa.shared::cluster.u32 r1, %0, 1;\n"
               "mbarrier.arrive.shared::cluster.b64 _, [r0];\n"
               "mbarrier.arrive.shared::cluster.b64 _, [r1];\n}"
               :: "r"(bar) : "memory");
}
__device__ __forceinline__ void mbar_wait(uint32_t bar, uint32_t parity) {
  asm volatile("{\n.reg .pred P1;\n.reg .u32 cnt;\nmov.u32 cnt, 0;\n"
               "LAB_WAIT:\n"
               "mbarrier.try_wait.parity.shared::cta.b64 P1, [%0], %1;\n"
               "@P1 bra DONE;\n"
               "add.u32 cnt, cnt, 1;\n"
               "setp.lt.u32 P1, cnt, 16777216;\n"
               "@P1 bra LAB_WAIT;\n"
               "trap;\n"
               "DONE:\n}"
               :: "r"(bar), "r"(parity) : "memory");
}
__device__ __forceinline__ uint64_t policy_evict_first() {
  uint64_t p; asm volatile("createpolicy.fractional.L2::evict_first.b64 %0, 1.0;" : "=l"(p)); return p;
}
__device__ __forceinline__ void tma_2d_mc(uint32_t dst, const CUtensorMap* m, uint32_t bar, int c0, int c1, uint64_t pol) {
  asm volatile("cp.async.bulk.tensor.2d.shared::cluster.global.mbarrier::complete_tx::bytes.multicast::cluster.L2::cache_hint [%0], [%1, {%3, %4}], [%2], %5, %6;"
               :: "r"(dst), "l"(m), "r"(bar), "r"(c0), "r"(c1), "h"((uint16_t)3), "l"(pol) : "memory");
}
__device__ __forceinline__ void tma_2d_nohint(uint32_t dst, const CUtensorMap* m, uint32_t bar, int c0, int c1) {
  asm volatile("cp.async.bulk.tensor.2d.shared::cluster.global.mbarrier::complete_tx::bytes [%0], [%1, {%3, %4}], [%2];"
               :: "r"(dst), "l"(m), "r"(bar), "r"(c0), "r"(c1) : "memory");
}
__device__ __forceinline__ void tma_2d_mc_nohint(uint32_t dst, const CUtensorMap* m, uint32_t bar, int c0, int c1) {
  asm volatile("cp.async.bulk.tensor.2d.shared::cluster.global.mbarrier::complete_tx::bytes.multicast::cluster [%0], [%1, {%3, %4}], [%2], %5;"
               :: "r"(dst), "l"(m), "r"(bar), "r"(c0), "r"(c1), "h"((uint16_t)3) : "memory");
}
__device__ __forceinline__ void tma_2d(uint32_t dst, const CUtensorMap* m, uint32_t bar, int c0, int c1, uint64_t pol) {
  asm volatile("cp.async.bulk.tensor.2d.shared::cluster.global.mbarrier::complete_tx::bytes.L2::cache_hint [%0], [%1, {%3, %4}], [%2], %5;"
               :: "r"(dst), "l"(m), "r"(bar), "r"(c0), "r"(c1), "l"(pol) : "memory");
}
__device__ __forceinline__ void tma_3d(uint32_t dst, const CUtensorMap* m, uint32_t bar, int c0, int c1, int c2, uint64_t pol) {
  asm volatile("cp.async.bulk.tensor.3d.shared::cluster.global.mbarrier::complete_tx::bytes.L2::cache_hint [%0], [%1, {%3, %4, %5}], [%2], %6;"
               :: "r"(dst), "l"(m), "r"(bar), "r"(c0), "r"(c1), "r"(c2), "l"(pol) : "memory");
}
__device__ __forceinline__ void tma_store_2d(const CUtensorMap* m, uint32_t src, int c0, int c1) {
  asm volatile("cp.async.bulk.tensor.2d.global.shared::cta.bulk_group [%0, {%2, %3}], [%1];"
               :: "l"(m), "r"(src), "r"(c0), "r"(c1) : "memory");
}
__device__ __forceinline__ bool mbar_test(uint32_t bar, uint32_t parity) {
  uint32_t ok;
  asm volatile("{\n.reg .pred p;\nmbarrier.test_wait.parity.shared::cta.b64 p, [%1], %2;\nselp.u32 %0, 1, 0, p;\n}"
               : "=r"(ok) : "r"(bar), "r"(parity) : "memory");
  return ok;
}
__device__ __forceinline__ int lane_id() { int l; asm volatile("mov.u32 %0, %%laneid;" : "=r"(l)); return l; }
__device__ __forceinline__ unsigned long long gtimer() { unsigned long long g; asm volatile("mov.u64 %0, %%globaltimer;" : "=l"(g)); return g; }
__device__ __forceinline__ void tick() {
}
__device__ __forceinline__ void wait_until(unsigned long long t) {
#pragma unroll 1
  for (int i = 0; i < (1 << 20); i++) { if (gtimer() >= t) break; __nanosleep(40); }
}
__device__ __forceinline__ void mbar_arrive(uint32_t bar) {
  asm volatile("mbarrier.arrive.shared::cta.b64 _, [%0];" :: "r"(bar) : "memory");
}
__device__ __forceinline__ void wg_fence()  { asm volatile("wgmma.fence.sync.aligned;" ::: "memory"); }
__device__ __forceinline__ void wg_commit() { asm volatile("wgmma.commit_group.sync.aligned;" ::: "memory"); }
template <int N> __device__ __forceinline__ void wg_wait() { asm volatile("wgmma.wait_group.sync.aligned %0;" :: "n"(N) : "memory"); }
__device__ __forceinline__ void tok_wait(int id) { if (ORDER) asm volatile("bar.sync %0, 256;" :: "r"(id) : "memory"); }
__device__ __forceinline__ void tok_pass(int id) { if (ORDER) asm volatile("bar.arrive %0, 256;" :: "r"(id) : "memory"); }
__device__ __forceinline__ void bar_sync(int id, int n)   { asm volatile("bar.sync %0, %1;" :: "r"(id), "r"(n) : "memory"); }
__device__ __forceinline__ void cluster_arrive_relaxed() { asm volatile("barrier.cluster.arrive.relaxed.aligned;" ::: "memory"); }
__device__ __forceinline__ void cluster_wait()           { asm volatile("barrier.cluster.wait.aligned;" ::: "memory"); }
__device__ __forceinline__ unsigned ld_relaxed(const unsigned* p) {
  unsigned v; asm volatile("ld.relaxed.gpu.global.u32 %0, [%1];" : "=r"(v) : "l"(p) : "memory"); return v;
}
__device__ __forceinline__ unsigned ld_acquire(const unsigned* p) {
  unsigned v; asm volatile("ld.acquire.gpu.global.u32 %0, [%1];" : "=r"(v) : "l"(p) : "memory"); return v;
}
__device__ __forceinline__ void red_release_add(unsigned* p, unsigned v) {
  asm volatile("red.release.gpu.global.add.u32 [%0], %1;" :: "l"(p), "r"(v) : "memory");
}
__device__ __forceinline__ void spin_until(const unsigned* p, unsigned target) {
  asm volatile("{\n.reg .pred P1;\n.reg .u32 cnt, v;\nmov.u32 cnt, 0;\n"
               "LAB_SPIN:\n"
               "ld.acquire.gpu.global.u32 v, [%0];\n"
               "sub.u32 v, v, %1;\n"
               "setp.ge.s32 P1, v, 0;\n"
               "@P1 bra DONE;\n"
               "nanosleep.u32 20;\n"
               "add.u32 cnt, cnt, 1;\n"
               "setp.lt.u32 P1, cnt, 4194304;\n"
               "@P1 bra LAB_SPIN;\n"
               "trap;\n"
               "DONE:\n}"
               :: "l"(p), "r"(target) : "memory");
}
__device__ __forceinline__ uint32_t desc_lo(uint32_t addr, uint32_t lbo) { return ((addr & 0x3FFFF) >> 4) | ((lbo >> 4) << 16); }
__device__ __forceinline__ uint64_t desc(uint32_t lo, uint32_t byte_off = 0, uint32_t hi = 0x40000040u) {
  uint64_t d;
  asm("mov.b64 %0, {%1, %2};" : "=l"(d) : "r"(lo + (byte_off >> 4)), "r"(hi));
  return d;
}
__device__ __forceinline__ uint32_t pack_bf16(float lo, float hi) {
  uint32_t r; asm("cvt.rn.bf16x2.f32 %0, %1, %2;" : "=r"(r) : "f"(hi), "f"(lo)); return r;
}
__device__ __forceinline__ float ex2(float x) { float r; asm("ex2.approx.ftz.f32 %0, %1;" : "=f"(r) : "f"(x)); return r; }

__device__ __forceinline__ void wgmma_ss_n192_tb1(float (&d)[96], uint64_t descA, uint64_t descB) {
  asm volatile("{\n.reg .pred p;\n"
    "setp.ne.b32 p, 1, 0;\n"
    "wgmma.mma_async.sync.aligned.m64n192k16.f32.bf16.bf16 "
    "{%0, %1, %2, %3, %4, %5, %6, %7, %8, %9, %10, %11, %12, %13, %14, %15, "
    "%16, %17, %18, %19, %20, %21, %22, %23, %24, %25, %26, %27, %28, %29, %30, %31, "
    "%32, %33, %34, %35, %36, %37, %38, %39, %40, %41, %42, %43, %44, %45, %46, %47, "
    "%48, %49, %50, %51, %52, %53, %54, %55, %56, %57, %58, %59, %60, %61, %62, %63, "
    "%64, %65, %66, %67, %68, %69, %70, %71, %72, %73, %74, %75, %76, %77, %78, %79, "
    "%80, %81, %82, %83, %84, %85, %86, %87, %88, %89, %90, %91, %92, %93, %94, %95}, "
    "%96, %97, p, 1, 1, 0, 1;\n}\n"
    : "+f"(d[0]), "+f"(d[1]), "+f"(d[2]), "+f"(d[3]), "+f"(d[4]), "+f"(d[5]), "+f"(d[6]), "+f"(d[7]),
      "+f"(d[8]), "+f"(d[9]), "+f"(d[10]), "+f"(d[11]), "+f"(d[12]), "+f"(d[13]), "+f"(d[14]), "+f"(d[15]),
      "+f"(d[16]), "+f"(d[17]), "+f"(d[18]), "+f"(d[19]), "+f"(d[20]), "+f"(d[21]), "+f"(d[22]), "+f"(d[23]),
      "+f"(d[24]), "+f"(d[25]), "+f"(d[26]), "+f"(d[27]), "+f"(d[28]), "+f"(d[29]), "+f"(d[30]), "+f"(d[31]),
      "+f"(d[32]), "+f"(d[33]), "+f"(d[34]), "+f"(d[35]), "+f"(d[36]), "+f"(d[37]), "+f"(d[38]), "+f"(d[39]),
      "+f"(d[40]), "+f"(d[41]), "+f"(d[42]), "+f"(d[43]), "+f"(d[44]), "+f"(d[45]), "+f"(d[46]), "+f"(d[47]),
      "+f"(d[48]), "+f"(d[49]), "+f"(d[50]), "+f"(d[51]), "+f"(d[52]), "+f"(d[53]), "+f"(d[54]), "+f"(d[55]),
      "+f"(d[56]), "+f"(d[57]), "+f"(d[58]), "+f"(d[59]), "+f"(d[60]), "+f"(d[61]), "+f"(d[62]), "+f"(d[63]),
      "+f"(d[64]), "+f"(d[65]), "+f"(d[66]), "+f"(d[67]), "+f"(d[68]), "+f"(d[69]), "+f"(d[70]), "+f"(d[71]),
      "+f"(d[72]), "+f"(d[73]), "+f"(d[74]), "+f"(d[75]), "+f"(d[76]), "+f"(d[77]), "+f"(d[78]), "+f"(d[79]),
      "+f"(d[80]), "+f"(d[81]), "+f"(d[82]), "+f"(d[83]), "+f"(d[84]), "+f"(d[85]), "+f"(d[86]), "+f"(d[87]),
      "+f"(d[88]), "+f"(d[89]), "+f"(d[90]), "+f"(d[91]), "+f"(d[92]), "+f"(d[93]), "+f"(d[94]), "+f"(d[95])
    : "l"(descA), "l"(descB));
}

__device__ __forceinline__ void wgmma_ss_n192_tb1_init(float (&d)[96], uint64_t descA, uint64_t descB) {
  asm volatile("{\n.reg .pred p;\n"
    "setp.ne.b32 p, 0, 0;\n"
    "wgmma.mma_async.sync.aligned.m64n192k16.f32.bf16.bf16 "
    "{%0, %1, %2, %3, %4, %5, %6, %7, %8, %9, %10, %11, %12, %13, %14, %15, "
    "%16, %17, %18, %19, %20, %21, %22, %23, %24, %25, %26, %27, %28, %29, %30, %31, "
    "%32, %33, %34, %35, %36, %37, %38, %39, %40, %41, %42, %43, %44, %45, %46, %47, "
    "%48, %49, %50, %51, %52, %53, %54, %55, %56, %57, %58, %59, %60, %61, %62, %63, "
    "%64, %65, %66, %67, %68, %69, %70, %71, %72, %73, %74, %75, %76, %77, %78, %79, "
    "%80, %81, %82, %83, %84, %85, %86, %87, %88, %89, %90, %91, %92, %93, %94, %95}, "
    "%96, %97, p, 1, 1, 0, 1;\n}\n"
    : "=f"(d[0]), "=f"(d[1]), "=f"(d[2]), "=f"(d[3]), "=f"(d[4]), "=f"(d[5]), "=f"(d[6]), "=f"(d[7]),
      "=f"(d[8]), "=f"(d[9]), "=f"(d[10]), "=f"(d[11]), "=f"(d[12]), "=f"(d[13]), "=f"(d[14]), "=f"(d[15]),
      "=f"(d[16]), "=f"(d[17]), "=f"(d[18]), "=f"(d[19]), "=f"(d[20]), "=f"(d[21]), "=f"(d[22]), "=f"(d[23]),
      "=f"(d[24]), "=f"(d[25]), "=f"(d[26]), "=f"(d[27]), "=f"(d[28]), "=f"(d[29]), "=f"(d[30]), "=f"(d[31]),
      "=f"(d[32]), "=f"(d[33]), "=f"(d[34]), "=f"(d[35]), "=f"(d[36]), "=f"(d[37]), "=f"(d[38]), "=f"(d[39]),
      "=f"(d[40]), "=f"(d[41]), "=f"(d[42]), "=f"(d[43]), "=f"(d[44]), "=f"(d[45]), "=f"(d[46]), "=f"(d[47]),
      "=f"(d[48]), "=f"(d[49]), "=f"(d[50]), "=f"(d[51]), "=f"(d[52]), "=f"(d[53]), "=f"(d[54]), "=f"(d[55]),
      "=f"(d[56]), "=f"(d[57]), "=f"(d[58]), "=f"(d[59]), "=f"(d[60]), "=f"(d[61]), "=f"(d[62]), "=f"(d[63]),
      "=f"(d[64]), "=f"(d[65]), "=f"(d[66]), "=f"(d[67]), "=f"(d[68]), "=f"(d[69]), "=f"(d[70]), "=f"(d[71]),
      "=f"(d[72]), "=f"(d[73]), "=f"(d[74]), "=f"(d[75]), "=f"(d[76]), "=f"(d[77]), "=f"(d[78]), "=f"(d[79]),
      "=f"(d[80]), "=f"(d[81]), "=f"(d[82]), "=f"(d[83]), "=f"(d[84]), "=f"(d[85]), "=f"(d[86]), "=f"(d[87]),
      "=f"(d[88]), "=f"(d[89]), "=f"(d[90]), "=f"(d[91]), "=f"(d[92]), "=f"(d[93]), "=f"(d[94]), "=f"(d[95])
    : "l"(descA), "l"(descB));
}

__device__ __forceinline__ void wgmma_ss_n160_tb1(float (&d)[80], uint64_t descA, uint64_t descB) {
  asm volatile("{\n.reg .pred p;\n"
    "setp.ne.b32 p, 1, 0;\n"
    "wgmma.mma_async.sync.aligned.m64n160k16.f32.bf16.bf16 "
    "{%0, %1, %2, %3, %4, %5, %6, %7, %8, %9, %10, %11, %12, %13, %14, %15, "
    "%16, %17, %18, %19, %20, %21, %22, %23, %24, %25, %26, %27, %28, %29, %30, %31, "
    "%32, %33, %34, %35, %36, %37, %38, %39, %40, %41, %42, %43, %44, %45, %46, %47, "
    "%48, %49, %50, %51, %52, %53, %54, %55, %56, %57, %58, %59, %60, %61, %62, %63, "
    "%64, %65, %66, %67, %68, %69, %70, %71, %72, %73, %74, %75, %76, %77, %78, %79}, "
    "%80, %81, p, 1, 1, 0, 1;\n}\n"
    : "+f"(d[0]), "+f"(d[1]), "+f"(d[2]), "+f"(d[3]), "+f"(d[4]), "+f"(d[5]), "+f"(d[6]), "+f"(d[7]),
      "+f"(d[8]), "+f"(d[9]), "+f"(d[10]), "+f"(d[11]), "+f"(d[12]), "+f"(d[13]), "+f"(d[14]), "+f"(d[15]),
      "+f"(d[16]), "+f"(d[17]), "+f"(d[18]), "+f"(d[19]), "+f"(d[20]), "+f"(d[21]), "+f"(d[22]), "+f"(d[23]),
      "+f"(d[24]), "+f"(d[25]), "+f"(d[26]), "+f"(d[27]), "+f"(d[28]), "+f"(d[29]), "+f"(d[30]), "+f"(d[31]),
      "+f"(d[32]), "+f"(d[33]), "+f"(d[34]), "+f"(d[35]), "+f"(d[36]), "+f"(d[37]), "+f"(d[38]), "+f"(d[39]),
      "+f"(d[40]), "+f"(d[41]), "+f"(d[42]), "+f"(d[43]), "+f"(d[44]), "+f"(d[45]), "+f"(d[46]), "+f"(d[47]),
      "+f"(d[48]), "+f"(d[49]), "+f"(d[50]), "+f"(d[51]), "+f"(d[52]), "+f"(d[53]), "+f"(d[54]), "+f"(d[55]),
      "+f"(d[56]), "+f"(d[57]), "+f"(d[58]), "+f"(d[59]), "+f"(d[60]), "+f"(d[61]), "+f"(d[62]), "+f"(d[63]),
      "+f"(d[64]), "+f"(d[65]), "+f"(d[66]), "+f"(d[67]), "+f"(d[68]), "+f"(d[69]), "+f"(d[70]), "+f"(d[71]),
      "+f"(d[72]), "+f"(d[73]), "+f"(d[74]), "+f"(d[75]), "+f"(d[76]), "+f"(d[77]), "+f"(d[78]), "+f"(d[79])
    : "l"(descA), "l"(descB));
}

__device__ __forceinline__ void wgmma_ss_n160_tb1_init(float (&d)[80], uint64_t descA, uint64_t descB) {
  asm volatile("{\n.reg .pred p;\n"
    "setp.ne.b32 p, 0, 0;\n"
    "wgmma.mma_async.sync.aligned.m64n160k16.f32.bf16.bf16 "
    "{%0, %1, %2, %3, %4, %5, %6, %7, %8, %9, %10, %11, %12, %13, %14, %15, "
    "%16, %17, %18, %19, %20, %21, %22, %23, %24, %25, %26, %27, %28, %29, %30, %31, "
    "%32, %33, %34, %35, %36, %37, %38, %39, %40, %41, %42, %43, %44, %45, %46, %47, "
    "%48, %49, %50, %51, %52, %53, %54, %55, %56, %57, %58, %59, %60, %61, %62, %63, "
    "%64, %65, %66, %67, %68, %69, %70, %71, %72, %73, %74, %75, %76, %77, %78, %79}, "
    "%80, %81, p, 1, 1, 0, 1;\n}\n"
    : "=f"(d[0]), "=f"(d[1]), "=f"(d[2]), "=f"(d[3]), "=f"(d[4]), "=f"(d[5]), "=f"(d[6]), "=f"(d[7]),
      "=f"(d[8]), "=f"(d[9]), "=f"(d[10]), "=f"(d[11]), "=f"(d[12]), "=f"(d[13]), "=f"(d[14]), "=f"(d[15]),
      "=f"(d[16]), "=f"(d[17]), "=f"(d[18]), "=f"(d[19]), "=f"(d[20]), "=f"(d[21]), "=f"(d[22]), "=f"(d[23]),
      "=f"(d[24]), "=f"(d[25]), "=f"(d[26]), "=f"(d[27]), "=f"(d[28]), "=f"(d[29]), "=f"(d[30]), "=f"(d[31]),
      "=f"(d[32]), "=f"(d[33]), "=f"(d[34]), "=f"(d[35]), "=f"(d[36]), "=f"(d[37]), "=f"(d[38]), "=f"(d[39]),
      "=f"(d[40]), "=f"(d[41]), "=f"(d[42]), "=f"(d[43]), "=f"(d[44]), "=f"(d[45]), "=f"(d[46]), "=f"(d[47]),
      "=f"(d[48]), "=f"(d[49]), "=f"(d[50]), "=f"(d[51]), "=f"(d[52]), "=f"(d[53]), "=f"(d[54]), "=f"(d[55]),
      "=f"(d[56]), "=f"(d[57]), "=f"(d[58]), "=f"(d[59]), "=f"(d[60]), "=f"(d[61]), "=f"(d[62]), "=f"(d[63]),
      "=f"(d[64]), "=f"(d[65]), "=f"(d[66]), "=f"(d[67]), "=f"(d[68]), "=f"(d[69]), "=f"(d[70]), "=f"(d[71]),
      "=f"(d[72]), "=f"(d[73]), "=f"(d[74]), "=f"(d[75]), "=f"(d[76]), "=f"(d[77]), "=f"(d[78]), "=f"(d[79])
    : "l"(descA), "l"(descB));
}

__device__ __forceinline__ void wgmma_rs_n96_tb0(float (&d)[48], uint32_t a0, uint32_t a1, uint32_t a2, uint32_t a3, uint64_t descB) {
  asm volatile("{\n.reg .pred p;\n"
    "setp.ne.b32 p, 1, 0;\n"
    "wgmma.mma_async.sync.aligned.m64n96k16.f32.bf16.bf16 "
    "{%0, %1, %2, %3, %4, %5, %6, %7, %8, %9, %10, %11, %12, %13, %14, %15, "
    "%16, %17, %18, %19, %20, %21, %22, %23, %24, %25, %26, %27, %28, %29, %30, %31, "
    "%32, %33, %34, %35, %36, %37, %38, %39, %40, %41, %42, %43, %44, %45, %46, %47}, "
    "{%48, %49, %50, %51}, %52, p, 1, 1, 0;\n}\n"
    : "+f"(d[0]), "+f"(d[1]), "+f"(d[2]), "+f"(d[3]), "+f"(d[4]), "+f"(d[5]), "+f"(d[6]), "+f"(d[7]),
      "+f"(d[8]), "+f"(d[9]), "+f"(d[10]), "+f"(d[11]), "+f"(d[12]), "+f"(d[13]), "+f"(d[14]), "+f"(d[15]),
      "+f"(d[16]), "+f"(d[17]), "+f"(d[18]), "+f"(d[19]), "+f"(d[20]), "+f"(d[21]), "+f"(d[22]), "+f"(d[23]),
      "+f"(d[24]), "+f"(d[25]), "+f"(d[26]), "+f"(d[27]), "+f"(d[28]), "+f"(d[29]), "+f"(d[30]), "+f"(d[31]),
      "+f"(d[32]), "+f"(d[33]), "+f"(d[34]), "+f"(d[35]), "+f"(d[36]), "+f"(d[37]), "+f"(d[38]), "+f"(d[39]),
      "+f"(d[40]), "+f"(d[41]), "+f"(d[42]), "+f"(d[43]), "+f"(d[44]), "+f"(d[45]), "+f"(d[46]), "+f"(d[47])
    : "r"(a0), "r"(a1), "r"(a2), "r"(a3), "l"(descB));
}

__device__ __forceinline__ void wgmma_rs_n96_tb0_init(float (&d)[48], uint32_t a0, uint32_t a1, uint32_t a2, uint32_t a3, uint64_t descB) {
  asm volatile("{\n.reg .pred p;\n"
    "setp.ne.b32 p, 0, 0;\n"
    "wgmma.mma_async.sync.aligned.m64n96k16.f32.bf16.bf16 "
    "{%0, %1, %2, %3, %4, %5, %6, %7, %8, %9, %10, %11, %12, %13, %14, %15, "
    "%16, %17, %18, %19, %20, %21, %22, %23, %24, %25, %26, %27, %28, %29, %30, %31, "
    "%32, %33, %34, %35, %36, %37, %38, %39, %40, %41, %42, %43, %44, %45, %46, %47}, "
    "{%48, %49, %50, %51}, %52, p, 1, 1, 0;\n}\n"
    : "=f"(d[0]), "=f"(d[1]), "=f"(d[2]), "=f"(d[3]), "=f"(d[4]), "=f"(d[5]), "=f"(d[6]), "=f"(d[7]),
      "=f"(d[8]), "=f"(d[9]), "=f"(d[10]), "=f"(d[11]), "=f"(d[12]), "=f"(d[13]), "=f"(d[14]), "=f"(d[15]),
      "=f"(d[16]), "=f"(d[17]), "=f"(d[18]), "=f"(d[19]), "=f"(d[20]), "=f"(d[21]), "=f"(d[22]), "=f"(d[23]),
      "=f"(d[24]), "=f"(d[25]), "=f"(d[26]), "=f"(d[27]), "=f"(d[28]), "=f"(d[29]), "=f"(d[30]), "=f"(d[31]),
      "=f"(d[32]), "=f"(d[33]), "=f"(d[34]), "=f"(d[35]), "=f"(d[36]), "=f"(d[37]), "=f"(d[38]), "=f"(d[39]),
      "=f"(d[40]), "=f"(d[41]), "=f"(d[42]), "=f"(d[43]), "=f"(d[44]), "=f"(d[45]), "=f"(d[46]), "=f"(d[47])
    : "r"(a0), "r"(a1), "r"(a2), "r"(a3), "l"(descB));
}

__device__ __forceinline__ void wgmma_rs_n128_tb1(float (&d)[64], uint32_t a0, uint32_t a1, uint32_t a2, uint32_t a3, uint64_t descB) {
  asm volatile("{\n.reg .pred p;\n"
    "setp.ne.b32 p, 1, 0;\n"
    "wgmma.mma_async.sync.aligned.m64n128k16.f32.bf16.bf16 "
    "{%0, %1, %2, %3, %4, %5, %6, %7, %8, %9, %10, %11, %12, %13, %14, %15, "
    "%16, %17, %18, %19, %20, %21, %22, %23, %24, %25, %26, %27, %28, %29, %30, %31, "
    "%32, %33, %34, %35, %36, %37, %38, %39, %40, %41, %42, %43, %44, %45, %46, %47, "
    "%48, %49, %50, %51, %52, %53, %54, %55, %56, %57, %58, %59, %60, %61, %62, %63}, "
    "{%64, %65, %66, %67}, %68, p, 1, 1, 1;\n}\n"
    : "+f"(d[0]), "+f"(d[1]), "+f"(d[2]), "+f"(d[3]), "+f"(d[4]), "+f"(d[5]), "+f"(d[6]), "+f"(d[7]),
      "+f"(d[8]), "+f"(d[9]), "+f"(d[10]), "+f"(d[11]), "+f"(d[12]), "+f"(d[13]), "+f"(d[14]), "+f"(d[15]),
      "+f"(d[16]), "+f"(d[17]), "+f"(d[18]), "+f"(d[19]), "+f"(d[20]), "+f"(d[21]), "+f"(d[22]), "+f"(d[23]),
      "+f"(d[24]), "+f"(d[25]), "+f"(d[26]), "+f"(d[27]), "+f"(d[28]), "+f"(d[29]), "+f"(d[30]), "+f"(d[31]),
      "+f"(d[32]), "+f"(d[33]), "+f"(d[34]), "+f"(d[35]), "+f"(d[36]), "+f"(d[37]), "+f"(d[38]), "+f"(d[39]),
      "+f"(d[40]), "+f"(d[41]), "+f"(d[42]), "+f"(d[43]), "+f"(d[44]), "+f"(d[45]), "+f"(d[46]), "+f"(d[47]),
      "+f"(d[48]), "+f"(d[49]), "+f"(d[50]), "+f"(d[51]), "+f"(d[52]), "+f"(d[53]), "+f"(d[54]), "+f"(d[55]),
      "+f"(d[56]), "+f"(d[57]), "+f"(d[58]), "+f"(d[59]), "+f"(d[60]), "+f"(d[61]), "+f"(d[62]), "+f"(d[63])
    : "r"(a0), "r"(a1), "r"(a2), "r"(a3), "l"(descB));
}

__device__ __forceinline__ void wgmma_rs_n128_tb1_init(float (&d)[64], uint32_t a0, uint32_t a1, uint32_t a2, uint32_t a3, uint64_t descB) {
  asm volatile("{\n.reg .pred p;\n"
    "setp.ne.b32 p, 0, 0;\n"
    "wgmma.mma_async.sync.aligned.m64n128k16.f32.bf16.bf16 "
    "{%0, %1, %2, %3, %4, %5, %6, %7, %8, %9, %10, %11, %12, %13, %14, %15, "
    "%16, %17, %18, %19, %20, %21, %22, %23, %24, %25, %26, %27, %28, %29, %30, %31, "
    "%32, %33, %34, %35, %36, %37, %38, %39, %40, %41, %42, %43, %44, %45, %46, %47, "
    "%48, %49, %50, %51, %52, %53, %54, %55, %56, %57, %58, %59, %60, %61, %62, %63}, "
    "{%64, %65, %66, %67}, %68, p, 1, 1, 1;\n}\n"
    : "=f"(d[0]), "=f"(d[1]), "=f"(d[2]), "=f"(d[3]), "=f"(d[4]), "=f"(d[5]), "=f"(d[6]), "=f"(d[7]),
      "=f"(d[8]), "=f"(d[9]), "=f"(d[10]), "=f"(d[11]), "=f"(d[12]), "=f"(d[13]), "=f"(d[14]), "=f"(d[15]),
      "=f"(d[16]), "=f"(d[17]), "=f"(d[18]), "=f"(d[19]), "=f"(d[20]), "=f"(d[21]), "=f"(d[22]), "=f"(d[23]),
      "=f"(d[24]), "=f"(d[25]), "=f"(d[26]), "=f"(d[27]), "=f"(d[28]), "=f"(d[29]), "=f"(d[30]), "=f"(d[31]),
      "=f"(d[32]), "=f"(d[33]), "=f"(d[34]), "=f"(d[35]), "=f"(d[36]), "=f"(d[37]), "=f"(d[38]), "=f"(d[39]),
      "=f"(d[40]), "=f"(d[41]), "=f"(d[42]), "=f"(d[43]), "=f"(d[44]), "=f"(d[45]), "=f"(d[46]), "=f"(d[47]),
      "=f"(d[48]), "=f"(d[49]), "=f"(d[50]), "=f"(d[51]), "=f"(d[52]), "=f"(d[53]), "=f"(d[54]), "=f"(d[55]),
      "=f"(d[56]), "=f"(d[57]), "=f"(d[58]), "=f"(d[59]), "=f"(d[60]), "=f"(d[61]), "=f"(d[62]), "=f"(d[63])
    : "r"(a0), "r"(a1), "r"(a2), "r"(a3), "l"(descB));
}

__device__ __forceinline__ void wgmma_rs_n64_tb1(float (&d)[32], uint32_t a0, uint32_t a1, uint32_t a2, uint32_t a3, uint64_t descB) {
  asm volatile("{\n.reg .pred p;\n"
    "setp.ne.b32 p, 1, 0;\n"
    "wgmma.mma_async.sync.aligned.m64n64k16.f32.bf16.bf16 "
    "{%0, %1, %2, %3, %4, %5, %6, %7, %8, %9, %10, %11, %12, %13, %14, %15, "
    "%16, %17, %18, %19, %20, %21, %22, %23, %24, %25, %26, %27, %28, %29, %30, %31}, "
    "{%32, %33, %34, %35}, %36, p, 1, 1, 1;\n}\n"
    : "+f"(d[0]), "+f"(d[1]), "+f"(d[2]), "+f"(d[3]), "+f"(d[4]), "+f"(d[5]), "+f"(d[6]), "+f"(d[7]),
      "+f"(d[8]), "+f"(d[9]), "+f"(d[10]), "+f"(d[11]), "+f"(d[12]), "+f"(d[13]), "+f"(d[14]), "+f"(d[15]),
      "+f"(d[16]), "+f"(d[17]), "+f"(d[18]), "+f"(d[19]), "+f"(d[20]), "+f"(d[21]), "+f"(d[22]), "+f"(d[23]),
      "+f"(d[24]), "+f"(d[25]), "+f"(d[26]), "+f"(d[27]), "+f"(d[28]), "+f"(d[29]), "+f"(d[30]), "+f"(d[31])
    : "r"(a0), "r"(a1), "r"(a2), "r"(a3), "l"(descB));
}

__device__ __forceinline__ void wgmma_rs_n64_tb1_init(float (&d)[32], uint32_t a0, uint32_t a1, uint32_t a2, uint32_t a3, uint64_t descB) {
  asm volatile("{\n.reg .pred p;\n"
    "setp.ne.b32 p, 0, 0;\n"
    "wgmma.mma_async.sync.aligned.m64n64k16.f32.bf16.bf16 "
    "{%0, %1, %2, %3, %4, %5, %6, %7, %8, %9, %10, %11, %12, %13, %14, %15, "
    "%16, %17, %18, %19, %20, %21, %22, %23, %24, %25, %26, %27, %28, %29, %30, %31}, "
    "{%32, %33, %34, %35}, %36, p, 1, 1, 1;\n}\n"
    : "=f"(d[0]), "=f"(d[1]), "=f"(d[2]), "=f"(d[3]), "=f"(d[4]), "=f"(d[5]), "=f"(d[6]), "=f"(d[7]),
      "=f"(d[8]), "=f"(d[9]), "=f"(d[10]), "=f"(d[11]), "=f"(d[12]), "=f"(d[13]), "=f"(d[14]), "=f"(d[15]),
      "=f"(d[16]), "=f"(d[17]), "=f"(d[18]), "=f"(d[19]), "=f"(d[20]), "=f"(d[21]), "=f"(d[22]), "=f"(d[23]),
      "=f"(d[24]), "=f"(d[25]), "=f"(d[26]), "=f"(d[27]), "=f"(d[28]), "=f"(d[29]), "=f"(d[30]), "=f"(d[31])
    : "r"(a0), "r"(a1), "r"(a2), "r"(a3), "l"(descB));
}

template <int V> struct Int { static constexpr int value = V; };

#define WAIT_FULL(R) do { PROF_USE_WG(1, (R).u); TR_WG(0x100 + (R).u); mbar_wait((R).full(full0), (R).phase()); TR_WG(0x200 + (R).u); PROF_USE_WG(2, (R).u); } while (0)

struct Ring {
  uint32_t u;
  __device__ __forceinline__ uint32_t slot()  const { return u & (NSLOT - 1); }
  __device__ __forceinline__ uint32_t phase() const { return (u >> 2) & 1; }
  __device__ __forceinline__ uint32_t full(uint32_t full0)   const { return full0 + 8 * slot(); }
  __device__ __forceinline__ uint32_t empty(uint32_t full0)  const { return full0 + 8 * NSLOT + 8 * slot(); }
  __device__ __forceinline__ uint32_t addr(uint32_t ring)    const { return ring + slot() * SLOT_BYTES; }
  __device__ __forceinline__ Ring operator+(uint32_t d) const { return Ring{u + d}; }
};

__device__ __forceinline__ void softmax96(float (&s)[48], uint32_t (&p)[24], float& r0, float& r1) {
  const float c = 0.07216878364870322f * 1.4426950408889634f;
  float a0[6], a1[6];
#pragma unroll
  for (int j = 0; j < 6; j++) {
    a0[j] = fmaxf(fmaxf(s[8 * j], s[8 * j + 1]), fmaxf(s[8 * j + 4], s[8 * j + 5]));
    a1[j] = fmaxf(fmaxf(s[8 * j + 2], s[8 * j + 3]), fmaxf(s[8 * j + 6], s[8 * j + 7]));
  }
  float m0 = fmaxf(fmaxf(fmaxf(a0[0], a0[1]), fmaxf(a0[2], a0[3])), fmaxf(a0[4], a0[5]));
  float m1 = fmaxf(fmaxf(fmaxf(a1[0], a1[1]), fmaxf(a1[2], a1[3])), fmaxf(a1[4], a1[5]));
  m0 = fmaxf(m0, __shfl_xor_sync(0xffffffffu, m0, 1));
  m1 = fmaxf(m1, __shfl_xor_sync(0xffffffffu, m1, 1));
  m0 = fmaxf(m0, __shfl_xor_sync(0xffffffffu, m0, 2));
  m1 = fmaxf(m1, __shfl_xor_sync(0xffffffffu, m1, 2));
  const float b0 = -m0 * c, b1 = -m1 * c;
  float l0 = 0.f, l1 = 0.f;
#pragma unroll
  for (int j = 0; j < 12; j++) {
    const float e0 = ex2(fmaf(s[4 * j],     c, b0)), e1 = ex2(fmaf(s[4 * j + 1], c, b0));
    const float e2 = ex2(fmaf(s[4 * j + 2], c, b1)), e3 = ex2(fmaf(s[4 * j + 3], c, b1));
    l0 += e0 + e1;
    l1 += e2 + e3;
    p[2 * j]     = pack_bf16(e0, e1);
    p[2 * j + 1] = pack_bf16(e2, e3);
  }
  l0 += __shfl_xor_sync(0xffffffffu, l0, 1);
  l1 += __shfl_xor_sync(0xffffffffu, l1, 1);
  l0 += __shfl_xor_sync(0xffffffffu, l0, 2);
  l1 += __shfl_xor_sync(0xffffffffu, l1, 2);
  asm("rcp.approx.ftz.f32 %0, %1;" : "=f"(r0) : "f"(l0));
  asm("rcp.approx.ftz.f32 %0, %1;" : "=f"(r1) : "f"(l1));
}

template <bool INIT>
__device__ __forceinline__ void qk_mma(float (&s)[48], const uint32_t (&qf)[48], uint32_t box0, uint32_t box1, uint32_t box2, int pass_id) {
  const uint32_t d0 = desc_lo(box0, 16), d1 = desc_lo(box1, 16), d2 = desc_lo(box2, 16);
  if (INIT) wgmma_rs_n96_tb0_init(s, qf[0], qf[1], qf[2], qf[3], desc(d0));
  else      wgmma_rs_n96_tb0(s, qf[0], qf[1], qf[2], qf[3], desc(d0));
#pragma unroll
  for (int k = 1; k < 12; k++) {
    wgmma_rs_n96_tb0(s, qf[4 * k], qf[4 * k + 1], qf[4 * k + 2], qf[4 * k + 3], desc(k < 4 ? d0 : k < 8 ? d1 : d2, (k & 3) * 32));
    if (k == TOK_S) tok_pass(pass_id);
  }
}
template <bool INIT>
__device__ __forceinline__ void pv_mma(float (&o)[96], const uint32_t (&pf)[24], uint32_t box01, uint32_t box2, int pass_id) {
  float (&oa)[64] = *reinterpret_cast<float (*)[64]>(&o[0]);
  float (&ob)[32] = *reinterpret_cast<float (*)[32]>(&o[64]);
  const uint32_t da = desc_lo(box01, 12288), db = desc_lo(box2, 12288);
  if (INIT) { wgmma_rs_n128_tb1_init(oa, pf[0], pf[1], pf[2], pf[3], desc(da)); wgmma_rs_n64_tb1_init(ob, pf[0], pf[1], pf[2], pf[3], desc(db)); }
  else      { wgmma_rs_n128_tb1(oa, pf[0], pf[1], pf[2], pf[3], desc(da));      wgmma_rs_n64_tb1(ob, pf[0], pf[1], pf[2], pf[3], desc(db)); }
#pragma unroll
  for (int k = 1; k < 6; k++) {
    wgmma_rs_n128_tb1(oa, pf[4 * k], pf[4 * k + 1], pf[4 * k + 2], pf[4 * k + 3], desc(da, k * 2048));
    wgmma_rs_n64_tb1(ob, pf[4 * k], pf[4 * k + 1], pf[4 * k + 2], pf[4 * k + 3], desc(db, k * 2048));
    if (k == TOK_P) tok_pass(pass_id);
  }
}

__global__ void __cluster_dims__(2, 1, 1) __launch_bounds__(NTHREADS, 1)
fused_attn_kernel(const __grid_constant__ Params prm, __nv_bfloat16* __restrict__ out) {
  extern __shared__ uint8_t smem_raw[];
  __shared__ uint64_t s_bars[2 * NSLOT + 10];
  __shared__ uint32_t s_dummy[64];
  __shared__ volatile uint32_t s_prog;

  const uint32_t ring = (smem_u32(smem_raw) + 1023) & ~1023u;
  const uint32_t stg  = ring + NSLOT * SLOT_BYTES;
  const uint32_t full0 = smem_u32(&s_bars[0]);
  const uint32_t o_done  = full0 + 16 * NSLOT;
  const uint32_t o_ready = o_done + 48;

  const int tid = threadIdx.x, lane = tid & 31;
  const int warp = __shfl_sync(0xffffffffu, tid >> 5, 0);
  const int rank = blockIdx.x & 1, cl = c_cluster_map[blockIdx.x >> 1], cta = 2 * cl + rank;
  const int grp = cl >> 3, prob = grp >> 2, bp = grp & 3, j8 = cl & 7;
  const int split = j8 >> 1;

  if (tid == 13 * 32) {
    asm volatile("prefetch.tensormap [%0];" :: "l"(&prm.wq[prob]) : "memory");
    asm volatile("prefetch.tensormap [%0];" :: "l"(&prm.x1[prob]) : "memory");
    asm volatile("prefetch.tensormap [%0];" :: "l"(&prm.x[prob]) : "memory");
  }
  if (tid == 12 * 32) {
#pragma unroll
    for (int s = 0; s < NSLOT; s++) { mbar_init(full0 + 8 * s, 1); mbar_init(full0 + 8 * NSLOT + 8 * s, 6); }
    for (int s = 0; s < 6; s++) mbar_init(o_done + 8 * s, 12);
    for (int s = 0; s < 4; s++) mbar_init(o_ready + 8 * s, 1);
    s_prog = NSLOT;
    asm volatile("fence.mbarrier_init.release.cluster;" ::: "memory");
  }
  __syncthreads();
  cluster_arrive_relaxed();
  if (tid == 12 * 32) {
    const int h = 2 * j8 + rank;
    const uint64_t pol = POL_STREAM();
#pragma unroll
    for (int s = 0; s < NSLOT; s++) {
      mbar_expect_tx(full0 + 8 * s, SLOT_BYTES);
      tma_2d_nohint(ring + s * SLOT_BYTES, &prm.x1[prob], full0 + 8 * s, 64 * s, 192 * bp);
      tma_3d(ring + s * SLOT_BYTES + B_OFF, &prm.wq[prob], full0 + 8 * s, 0, 64 * s, 3 * h, pol);
    }
  }
  __syncwarp();
  cluster_wait();

  if (warp >= 12) {
    asm volatile("setmaxnreg.dec.sync.aligned.u32 32;");
    if (warp == 12) {
      if (lane == 0) {
        Ring r{0};
        const uint64_t pol_s = POL_STREAM();
        const int ncol0 = 320 * (j8 & 1);
        TR_DECL;
        PROF(3, 1);
#pragma unroll 1
        for (int w = 0; w < 2; w++) {
          const int h = 16 * w + 2 * j8 + rank;
#pragma unroll 1
          for (int ks = 0; ks < 10; ks++) {
            const uint32_t fb = r.full(full0), sl = r.addr(ring);
            if (r.u >= NSLOT) {
              mbar_wait(r.empty(full0), r.phase() ^ 1);
              mbar_expect_tx(fb, SLOT_BYTES);
              PROF_USE(0, r.u);
              TR(3, 0x400 + r.u);
              s_prog = r.u;
              tick();
              tma_3d(sl + B_OFF, &prm.wq[prob], fb, 0, 64 * ks, 3 * h, pol_s);
              tma_2d_mc_nohint(sl + rank * 12288, &prm.x[prob], fb, 64 * ks, 192 * bp + 96 * rank);
            }
            r.u++;
          }
          PROF(3, 2 + 2 * w);
#pragma unroll 1
          for (int t = 0; t < 3; t++) {
            const uint32_t fb = r.full(full0), sl = r.addr(ring);
            const int row0 = ((2 * bp) * 32 + h) * 96, row1 = row0 + 32 * 96;
            mbar_wait(r.empty(full0), r.phase() ^ 1);
            mbar_expect_tx(fb, SLOT_BYTES);
            PROF_USE(0, r.u);
            TR(3, 0x400 + r.u);
            s_prog = r.u;
            if (t == 0) {
              tma_3d(sl,         &prm.k[prob],  fb, 0, row0, 0, pol_s);
              tma_3d(sl + 36864, &prm.k1[prob], fb, 0, row1, 0, pol_s);
            } else if (t == 1) {
              tma_3d(sl,         &prm.k1[prob], fb, 0, row1, 1, pol_s);
              tma_3d(sl + 12288, &prm.k1[prob], fb, 0, row1, 2, pol_s);
              tma_3d(sl + 24576, &prm.v1[prob], fb, 0, row0, 0, pol_s);
              tma_3d(sl + 36864, &prm.v1[prob], fb, 0, row0, 1, pol_s);
            } else {
              tma_3d(sl,         &prm.v1[prob], fb, 0, row0, 2, pol_s);
              tma_3d(sl + 12288, &prm.v[prob],  fb, 0, row1, 0, pol_s);
            }
            r.u++;
          }
          PROF(3, 3 + 2 * w);
        }
#pragma unroll 1
        for (int i = 0; i < 24; i++) {
          const int h = i < 12 ? 4 * split + i / 3 : 16 + 4 * split + (i & 3);
          const int c = i < 12 ? i % 3 : (i - 12) >> 2;
          const uint32_t fb = r.full(full0), sl = r.addr(ring);
          const int k0 = h * 192 + c * 64;
          mbar_wait(r.empty(full0), r.phase() ^ 1);
          mbar_expect_tx(fb, SLOT_BYTES);
          PROF_USE(0, r.u);
          TR(3, 0x400 + r.u);
          s_prog = r.u;
          tick();
          tma_2d(sl + B_OFF,         &prm.wo[prob],   fb, ncol0 + 192 * rank,      k0, pol_s);
          tma_2d(sl + B_OFF + 8192,  &prm.wo[prob],   fb, ncol0 + 192 * rank + 64, k0, pol_s);
          tma_2d(sl + B_OFF + 16384, &prm.wo[prob],   fb, ncol0 + 128, k0, pol_s);
          if (i == 0 || (i >= 12 && (i & 3) == 0)) {
            mbar_wait(o_ready + 8 * (i == 0 ? 0 : (i >> 2) - 2), 0);
            if (i == 0) PROF(3, 6);
            if (i == 12) PROF(3, 7);
          }
          tma_2d_mc(sl + rank * 12288, &prm.o_ld, fb, k0, prob * 768 + 192 * bp + 96 * rank, pol_s);
          r.u++;
        }
        PROF(3, 8);
      }
    } else if (warp == 13) {
      {
        const unsigned obase = 3u * ld_relaxed(&g_epoch[cta]);
        uint32_t pub = 0, wat = 0;
#pragma unroll 1
        for (int it = 0; it < (1 << 22) && (pub < 6 || wat < 4); it++) {
          if (pub < 6 && mbar_test(o_done + 8 * pub, 0)) {
            uint32_t n = 1;
            while ((pub + n) % 3 != 0 && mbar_test(o_done + 8 * (pub + n), 0)) n++;
            if (lane == 0) {
              if (pub == 0 || pub == 3) PROF(3, 9 + 2 * (pub / 3));
              red_release_add(&g_ready[grp * 32 + 16 * (pub >= 3) + 2 * j8 + rank], n);
              if (pub == 0 || pub == 3) PROF(3, 10 + 2 * (pub / 3));
            }
            __syncwarp();
            pub += n;
          } else if (wat < 4 && pub > wat + 2) {
            const unsigned tgt = obase + (wat == 0 ? 3u : wat);
            const unsigned a = ld_acquire(&g_ready[grp * 32 + (wat == 0 ? 0 : 16) + 4 * split + (lane & 3)]);
            if (__all_sync(0xffffffffu, (int)(a - tgt) >= 0)) {
              if (lane == 0) {
                asm volatile("fence.proxy.async;" ::: "memory");
                mbar_arrive(o_ready + 8 * wat);
                if (wat < 2) PROF(3, 13 + wat);
              }
              __syncwarp();
              wat++;
            }
          } else {
            __nanosleep(40);
          }
        }
      }
    } else {
      {
        const int h0 = 2 * j8 + rank;
        const uint8_t* xp  = prm.xptr[prob];
        const uint8_t* wqp = prm.wqptr[prob];
        const uint8_t* wop = prm.woptr[prob];
        auto addr_of = [&](int n) -> const uint8_t* {
          if (n < 3) {
            const int i = min(n * 32 + lane, 71);
            return xp + (size_t)(192 * bp + 12 * h0 + i % 12) * 1280 + (NSLOT + i / 12) * 128;
          }
          if (n < 12 || (n >= 48 && n < 63)) {
            const bool second = n >= 48;
            const int i = (second ? n - 48 : n - 3 + 6) * 32 + lane;
            const int ks = i / 48, rem = i - ks * 48;
            return wqp + (size_t)(64 * ks + 16 * bp + rem / 3) * 12288 + (h0 + (second ? 16 : 0)) * 384 + (rem % 3) * 128;
          }
          if (n < 99) {
            const bool second = n >= 63;
            const int m = second ? n - 63 : n - 12, tile = m / 9;
            const uint8_t* base = (tile < 2) ? prm.kptr[prob] : prm.vptr[prob];
            return base + (size_t)((2 * bp + (tile & 1)) * 32 + h0 + (second ? 16 : 0)) * KV_BYTES + (m - 9 * tile) * 4096 + lane * 128;
          }
          const int i = min((n - 99) * 32 + lane, 959), hh = i / 120, rem = i - hh * 120;
          const int h = (hh >> 2) * 16 + 4 * split + (hh & 3);
          return wop + (size_t)(h * 192 + 12 * (4 * bp + 2 * (j8 & 1) + rank) + rem / 10) * 1280 + (rem % 10) * 128;
        };
        auto use_of = [&](int n) -> int {
          if (n < 3)  return NSLOT + (n * 32) / 12;
          if (n < 12) return ((n + 3) * 32) / 48;
          if (n < 48) { const int t = (n - 12) / 9; return 10 + (t < 2 ? 0 : t - 1); }
          if (n < 63) return 13 + ((n - 48) * 32) / 48;
          if (n < 99) { const int t = (n - 63) / 9; return 23 + (t < 2 ? 0 : t - 1); }
          const int hh = ((n - 99) * 32) / 120;
          const int c = (12 * (4 * bp + 2 * (j8 & 1) + rank)) >> 6;
          return hh < 4 ? 26 + 3 * hh + c : 38 + 4 * c + (hh - 4);
        };
        auto release_of = [&](int n) -> int {
          if (n < 12) return 0;
          if (n < 48) return PF_R0 + ((n - 12) * (PF_R1 - PF_R0)) / 36;
          if (n < 63) return PF_R1 + ((n - 48) * (PF_R2 - PF_R1)) / 15;
          if (n < 99) return PF_R2 + ((n - 63) * (PF_R3 - PF_R2)) / 36;
          return PF_R3 + ((n - 99) * (PF_R4 - PF_R3)) / 30;
        };
        wait_until(gtimer() + PF_DELAY_NS);
        const uint32_t dummy = smem_u32(&s_dummy[tid & 63]);
#pragma unroll 1
        for (int n = warp - 14; n < 129; n += 2) {
          const int u = use_of(n), rel = release_of(n);
          int guard = 0;
          while ((int)s_prog < rel && ++guard < (1 << 20)) __nanosleep(100);
          if (n >= 99 + PF_WO_N) break;
          if ((int)s_prog < u)
            asm volatile("cp.async.ca.shared.global.L2::128B [%0], [%1], 4;" :: "r"(dummy), "l"(addr_of(n)) : "memory");
          asm volatile("cp.async.commit_group;" ::: "memory");
          asm volatile("cp.async.wait_group %0;" :: "n"(PF_WIN) : "memory");
        }
        asm volatile("cp.async.wait_group 0;" ::: "memory");
      }
    }
  } else {
    asm volatile("setmaxnreg.inc.sync.aligned.u32 160;");
    const int wg = warp >> 2, wq4 = warp & 3;
    const bool elected = wq4 == 0 && lane_id() == 0;
    const uint32_t descA0 = desc_lo(ring + wg * 8192, 16), descB0 = desc_lo(ring + B_OFF, 8192);
    Ring r{0};
    TR_DECL;
    TR_WG(1);
    PROF_WG(0);
    uint32_t pend[32];
    const uint32_t wstg = stg + warp * 2048;
    auto stg_acquire = [&]() {
      if (lane_id() == 0) asm volatile("cp.async.bulk.wait_group.read 0;" ::: "memory");
      __syncwarp();
    };
    auto stage_in = [&](const uint32_t* v) {
      stg_acquire();
      const int lane = lane_id(), r8 = lane & 7;
      const uint32_t st_base = wstg + (((lane >> 3) & 1) * 8 + r8) * 128;
#pragma unroll
      for (int jj = 0; jj < 4; jj++) {
        const uint32_t addr = st_base + (((2 * jj + (lane >> 4)) ^ r8) << 4);
        asm volatile("stmatrix.sync.aligned.m8n8.x4.shared.b16 [%0], {%1, %2, %3, %4};"
                     :: "r"(addr), "r"(v[4 * jj]), "r"(v[4 * jj + 1]), "r"(v[4 * jj + 2]), "r"(v[4 * jj + 3]) : "memory");
      }
    };
    auto send = [&](int wv, int box) {
      asm volatile("fence.proxy.async.shared::cta;" ::: "memory");
      __syncwarp();
      if (lane_id() == 0) {
        tma_store_2d(&prm.o_st, wstg, (16 * wv + 2 * j8 + rank) * 192 + 64 * box, prob * 768 + 192 * bp + 16 * warp);
        asm volatile("cp.async.bulk.commit_group;" ::: "memory");
      }
    };
    auto landed = [&](int ev, auto pending) {
      if (lane_id() == 0) {
        asm volatile("cp.async.bulk.wait_group %0;" :: "n"(decltype(pending)::value) : "memory");
        mbar_arrive(o_done + 8 * ev);
      }
    };

#pragma unroll 1
    for (int w = 0; w < 2; w++) {
      uint32_t qf[48];
      {
        float acc[96];
        {
          const uint32_t da = descA0 + r.slot() * (SLOT_BYTES >> 4), db = descB0 + r.slot() * (SLOT_BYTES >> 4);
          WAIT_FULL(r);
          if (w == 0) PROF_WG(1);
          if (w > 0) { if (wg == 0) tok_wait(14); else if (wg == 2) tok_wait(15); }
          wg_fence();
          wgmma_ss_n192_tb1_init(acc, desc(da), desc(db));
#pragma unroll
          for (int k = 1; k < 4; k++) wgmma_ss_n192_tb1(acc, desc(da, k * 32), desc(db, k * 2048));
          wg_commit();
          if (w > 0 && wg == 0) tok_pass(15);
          if (w > 0) send(0, 0);
          r.u++;
        }
#pragma unroll 1
        for (int ks = 1; ks < 10; ks++) {
          const uint32_t da = descA0 + r.slot() * (SLOT_BYTES >> 4), db = descB0 + r.slot() * (SLOT_BYTES >> 4);
          WAIT_FULL(r);
          if (ks == 9) { if (wg == 0) tok_wait(4); else if (wg == 2) tok_wait(5); }
          wg_fence();
          wgmma_ss_n192_tb1(acc, desc(da), desc(db));
          wg_commit();
          wg_wait<1>();
          TR_WG(0x300 + r.u - 1);
          if (elected) mbar_arrive_both(Ring{r.u - 1}.empty(full0));
#pragma unroll
          for (int k = 1; k < 4; k++) wgmma_ss_n192_tb1(acc, desc(da, k * 32), desc(db, k * 2048));
          wg_commit();
          if (ks == 9) tok_pass(wg == 1 ? 4 : wg == 0 ? 5 : 6);
          if (w > 0) {
            const int kk = wg == 1 ? ks - FL_LAG : ks;
            if (kk == FL_B1)      { stage_in(pend);      send(0, 1); }
            else if (kk == FL_B2) { stage_in(pend + 16); send(0, 2); }
            else if (kk == FL_LD) { landed(0, Int<0>{}); landed(1, Int<0>{}); landed(2, Int<0>{}); }
          }
          r.u++;
        }
        wg_wait<0>();
        if (elected) mbar_arrive_both(Ring{r.u - 1}.empty(full0));
        stg_acquire();
        const int lane = lane_id();
#pragma unroll
        for (int i = 0; i < 4; i++)
          asm volatile("st.shared.v4.u32 [%0], {%1, %2, %3, %4};"
                       :: "r"(wstg + i * 512 + lane * 16),
                          "r"(pack_bf16(acc[64 + 8 * i], acc[65 + 8 * i])), "r"(pack_bf16(acc[66 + 8 * i], acc[67 + 8 * i])),
                          "r"(pack_bf16(acc[68 + 8 * i], acc[69 + 8 * i])), "r"(pack_bf16(acc[70 + 8 * i], acc[71 + 8 * i])) : "memory");
#pragma unroll
        for (int i = 0; i < 32; i++) qf[i] = pack_bf16(acc[2 * i], acc[2 * i + 1]);
        asm volatile("" ::: "memory");
#pragma unroll
        for (int i = 0; i < 4; i++)
          asm volatile("ld.shared.v4.u32 {%0, %1, %2, %3}, [%4];"
                       : "=r"(qf[32 + 4 * i]), "=r"(qf[33 + 4 * i]), "=r"(qf[34 + 4 * i]), "=r"(qf[35 + 4 * i])
                       : "r"(wstg + i * 512 + lane * 16) : "memory");
      }
      PROF_WG(2 + 5 * w);
      TR_WG(2);
      const Ring rX = r, rY = r + 1, rZ = r + 2;
      r.u += 3;
      uint32_t pf[24];
      float rinv0, rinv1;
      const uint32_t aX = rX.addr(ring), aY = rY.addr(ring), aZ = rZ.addr(ring);
      {
        float s[48];
        WAIT_FULL(rX);
        if (wg == 2) WAIT_FULL(rY);
        tok_wait(wg == 1 ? 6 : wg == 0 ? 7 : 9);
        wg_fence();
        qk_mma<true>(s, qf, wg == 2 ? aX + 36864 : aX, wg == 2 ? aY : aX + 12288, wg == 2 ? aY + 12288 : aX + 24576, wg == 1 ? 7 : wg == 0 ? 8 : 10);
        wg_commit();
        wg_wait<0>();
        if (wg == 1) {
          if (wq4 < 2) {
#pragma unroll
            for (int i = 0; i < 48; i++) qf[i] = 0u;
          } else {
#pragma unroll
            for (int i = 0; i < 48; i++) s[i] = 0.f;
          }
          WAIT_FULL(rY);
          tok_wait(8);
          wg_fence();
          qk_mma<false>(s, qf, aX + 36864, aY, aY + 12288, 9);
          wg_commit();
          wg_wait<0>();
        }
        if (elected) { mbar_arrive_both(rX.empty(full0)); if (wg == 2) mbar_arrive_both(rY.empty(full0)); }
        __syncwarp();
        PROF_WG(3 + 5 * w);
        TR_WG(3);
        softmax96(s, pf, rinv0, rinv1);
      }
      PROF_WG(4 + 5 * w);
      TR_WG(4);
      float o[96];
      {
        if (wg == 0) WAIT_FULL(rY);
        WAIT_FULL(rZ);
        tok_wait(wg == 0 ? 10 : wg == 1 ? 11 : 12);
        wg_fence();
        pv_mma<true>(o, pf, wg == 2 ? aZ + 12288 : aY + 24576, wg == 2 ? aZ + 36864 : aZ, wg == 0 ? 11 : wg == 1 ? 12 : 13);
        wg_commit();
        wg_wait<0>();
        if (wg == 1) {
          if (elected) mbar_arrive_both(rY.empty(full0));
          if (wq4 < 2) {
#pragma unroll
            for (int i = 0; i < 24; i++) pf[i] = 0u;
          } else {
#pragma unroll
            for (int i = 0; i < 96; i++) o[i] = 0.f;
          }
          tok_wait(13);
          wg_fence();
          pv_mma<false>(o, pf, aZ + 12288, aZ + 36864, 14);
          wg_commit();
          wg_wait<0>();
        }
        if (elected) { if (wg == 0) mbar_arrive_both(rY.empty(full0)); mbar_arrive_both(rZ.empty(full0)); }
      }
      PROF_WG(5 + 5 * w);
      TR_WG(5);
      {
        uint32_t v[16];
#pragma unroll
        for (int i = 0; i < 16; i++) { const float ri = (i & 1) ? rinv1 : rinv0; v[i] = pack_bf16(o[2 * i] * ri, o[2 * i + 1] * ri); }
#pragma unroll
        for (int i = 0; i < 32; i++) { const float ri = (i & 1) ? rinv1 : rinv0; pend[i] = pack_bf16(o[32 + 2 * i] * ri, o[33 + 2 * i] * ri); }
        stage_in(v);
      }
      PROF_WG(6 + 5 * w);
      TR_WG(6);
    }

    const unsigned otarget = ld_relaxed(&g_epoch[cta]) + 1u, target = 3u * otarget;
    const uint32_t bhi = 0x40000040u | (rank ? 4u << 17 : 0u);
    float acc[80];
    {
      {
        const uint32_t da = descA0 + r.slot() * (SLOT_BYTES >> 4), db = descB0 + r.slot() * (SLOT_BYTES >> 4);
        WAIT_FULL(r);
        PROF_WG(12);
        if (wg == 0) tok_wait(14); else if (wg == 2) tok_wait(15);
        wg_fence();
        wgmma_ss_n160_tb1_init(acc, desc(da), desc(db, 0, bhi));
#pragma unroll
        for (int k = 1; k < 4; k++) wgmma_ss_n160_tb1(acc, desc(da, k * 32), desc(db, k * 2048, bhi));
        wg_commit();
        if (wg == 0) tok_pass(15);
        send(1, 0);
        r.u++;
      }
#pragma unroll 1
      for (int ks = 1; ks < 24; ks++) {
        const uint32_t da = descA0 + r.slot() * (SLOT_BYTES >> 4), db = descB0 + r.slot() * (SLOT_BYTES >> 4);
        const bool parked = TAIL_L > 0 && ks == 24 - TAIL_L && wg > 0;
        if (parked) {
          wg_wait<0>();
          if (ks <= 24 - NSLOT && elected) mbar_arrive_both(Ring{r.u - 1}.empty(full0));
          tok_wait(3 + wg);
        }
        WAIT_FULL(r);
        wg_fence();
        wgmma_ss_n160_tb1(acc, desc(da), desc(db, 0, bhi));
        wg_commit();
        wg_wait<1>();
        TR_WG(0x300 + r.u - 1);
        if (!parked && ks <= 24 - NSLOT && elected) mbar_arrive_both(Ring{r.u - 1}.empty(full0));
#pragma unroll
        for (int k = 1; k < 4; k++) wgmma_ss_n160_tb1(acc, desc(da, k * 32), desc(db, k * 2048, bhi));
        wg_commit();
        if (TAIL_L > 0 && ks == 23 && wg < 2) tok_pass(4 + wg);
        {
          const int kk = wg == 1 ? ks - FL2_LAG : ks;
          if (kk == FL2_B1)      { landed(3, Int<0>{}); stage_in(pend);      send(1, 1); }
          else if (kk == FL2_B2) { landed(4, Int<0>{}); stage_in(pend + 16); send(1, 2); }
          else if (kk == FL2_LD) { landed(5, Int<0>{}); }
        }
        r.u++;
      }
      wg_wait<0>();
    }
    PROF_WG(13);
    TR_WG(13);
    {
      const int lane = lane_id(), t = warp * 32 + lane;
#pragma unroll
      for (int q = 0; q < 4; q++) {
        const int blk0 = q == 0 ? 0 : q == 1 ? 6 : q == 2 ? 10 : 16, npk = (q & 1) ? 2 : 3;
        if (q != split) {
          const int dcta = (grp * 8 + 2 * q + (j8 & 1)) * 2 + rank;
          const int srcslot = split < q ? split : split - 1;
          uint4* dst = g_part + (size_t)(dcta * 3 + srcslot) * (3 * 384) + t;
#pragma unroll
          for (int i = 0; i < 3; i++) {
            if (i < npk) {
              const int a = 4 * blk0 + 8 * i;
              __stcg(dst + i * 384, make_uint4(pack_bf16(acc[a], acc[a + 1]), pack_bf16(acc[a + 2], acc[a + 3]),
                                               pack_bf16(acc[a + 4], acc[a + 5]), pack_bf16(acc[a + 6], acc[a + 7])));
            }
          }
        }
      }
      bar_sync(1 + wg, 128);
      if (wq4 == 0 && lane < 4 && lane != split) {
        const int q = lane;
        const int dcta = (grp * 8 + 2 * q + (j8 & 1)) * 2 + rank;
        red_release_add(&g_xflag[dcta * 3 + wg], 1u);
      }
      PROF_WG(14);
      TR_WG(14);
      const int nown = (split & 1) ? 2 : 3;
      float own[24];
#pragma unroll
      for (int i = 0; i < 24; i++)
        own[i] = split == 0 ? acc[i] : split == 1 ? acc[24 + (i & 15)] : split == 2 ? acc[40 + i] : acc[64 + (i & 15)];
      if (elected) spin_until(&g_xflag[cta * 3 + wg], target);
      bar_sync(1 + wg, 128);
      {
        const uint4* src = g_part + (size_t)(cta * 3) * (3 * 384) + t;
        uint4 v[9];
#pragma unroll
        for (int sidx = 0; sidx < 3; sidx++) {
          v[3 * sidx]     = __ldcg(src + (3 * sidx) * 384);
          v[3 * sidx + 1] = __ldcg(src + (3 * sidx + 1) * 384);
          v[3 * sidx + 2] = nown == 3 ? __ldcg(src + (3 * sidx + 2) * 384) : make_uint4(0u, 0u, 0u, 0u);
        }
#pragma unroll
        for (int sidx = 0; sidx < 3; sidx++) {
#pragma unroll
          for (int i = 0; i < 3; i++) {
            const uint32_t w[4] = {v[3 * sidx + i].x, v[3 * sidx + i].y, v[3 * sidx + i].z, v[3 * sidx + i].w};
#pragma unroll
            for (int k = 0; k < 4; k++) {
              own[8 * i + 2 * k]     += __uint_as_float(w[k] << 16);
              own[8 * i + 2 * k + 1] += __uint_as_float(w[k] & 0xffff0000u);
            }
          }
        }
      }
      stg_acquire();
      {
        const int r8 = lane & 7;
        const uint32_t st_base = wstg + (((lane >> 3) & 1) * 8 + r8) * 128;
#pragma unroll
        for (int jj = 0; jj < 3; jj++) {
          const uint32_t addr = st_base + (((2 * jj + (lane >> 4)) ^ r8) << 4);
          asm volatile("stmatrix.sync.aligned.m8n8.x4.shared.b16 [%0], {%1, %2, %3, %4};"
                       :: "r"(addr), "r"(pack_bf16(own[8 * jj], own[8 * jj + 1])), "r"(pack_bf16(own[8 * jj + 2], own[8 * jj + 3])),
                          "r"(pack_bf16(own[8 * jj + 4], own[8 * jj + 5])), "r"(pack_bf16(own[8 * jj + 6], own[8 * jj + 7])) : "memory");
        }
        __syncwarp();
        const int a0 = split == 0 ? 0 : split == 1 ? 48 : split == 2 ? 80 : 128;
        const int nch = 2 * nown;
        uint8_t* ob = reinterpret_cast<uint8_t*>(out) + ((size_t)(192 * bp + 16 * warp) * 1280 + 640 * prob + 320 * (j8 & 1)) * 2;
#pragma unroll
        for (int i = 0; i < 3; i++) {
          const int idx = i * 32 + lane;
          const int row = nown == 3 ? idx / 6 : idx >> 2, ch = idx - row * nch;
          if (row < 16) {
            uint4 w;
            asm volatile("ld.shared.v4.u32 {%0, %1, %2, %3}, [%4];" : "=r"(w.x), "=r"(w.y), "=r"(w.z), "=r"(w.w)
                         : "r"(wstg + row * 128 + ((ch ^ (row & 7)) << 4)) : "memory");
            const int a = a0 + 8 * ch;
            const int col = rank == 0 ? a : (a < 128 ? 192 + (a ^ 32) : 32 + a);
            *reinterpret_cast<uint4*>(ob + (size_t)row * 2560 + col * 2) = w;
          }
        }
      }
      if (t == 0) g_epoch[cta] = otarget;
    }
  }
}

typedef CUresult (*EncodeFn)(CUtensorMap*, CUtensorMapDataType, cuuint32_t, void*, const cuuint64_t*, const cuuint64_t*,
                             const cuuint32_t*, const cuuint32_t*, CUtensorMapInterleave, CUtensorMapSwizzle,
                             CUtensorMapL2promotion, CUtensorMapFloatOOBfill);

void make_map(EncodeFn enc, CUtensorMap* m, const void* ptr, int rank, const uint64_t* dims, const uint64_t* strides,
              const uint32_t* box) {
  cuuint64_t d[3], s[2]; cuuint32_t b[3], e[3] = {1, 1, 1};
  for (int i = 0; i < rank; i++) { d[i] = dims[i]; b[i] = box[i]; }
  for (int i = 0; i + 1 < rank; i++) s[i] = strides[i];
  enc(m, CU_TENSOR_MAP_DATA_TYPE_BFLOAT16, rank, const_cast<void*>(ptr), d, s, b, e, CU_TENSOR_MAP_INTERLEAVE_NONE,
      CU_TENSOR_MAP_SWIZZLE_128B, CU_TENSOR_MAP_L2_PROMOTION_L2_128B, CU_TENSOR_MAP_FLOAT_OOB_FILL_NONE);
}

}

extern "C" void kernel_launch(void* const* d_in, const int* in_sizes, int n_in, void* d_out, int out_size) {
  (void)in_sizes; (void)n_in; (void)out_size;
  static EncodeFn enc = nullptr;
  static void* o_ptr = nullptr;
  if (!enc) {
    void* fn = nullptr; cudaDriverEntryPointQueryResult st;
    cudaGetDriverEntryPoint("cuTensorMapEncodeTiled", &fn, cudaEnableDefault, &st);
    enc = (EncodeFn)fn;
    cudaGetSymbolAddress(&o_ptr, g_O);
    cudaFuncSetAttribute(fused_attn_kernel, cudaFuncAttributeMaxDynamicSharedMemorySize, SMEM_BYTES);
  }
  Params prm;
  for (int p = 0; p < 2; p++) {
    const void* x = d_in[5 * p + 0]; const void* k = d_in[5 * p + 1]; const void* v = d_in[5 * p + 2];
    const void* wq = d_in[5 * p + 3]; const void* wo = d_in[5 * p + 4];
    { uint64_t d[2] = {640, 768}, s[1] = {1280};              uint32_t b[2] = {64, 96};    make_map(enc, &prm.x[p],  x,  2, d, s, b); }
    { uint64_t d[2] = {640, 768}, s[1] = {1280};              uint32_t b[2] = {64, 192};   make_map(enc, &prm.x1[p], x,  2, d, s, b); }
    { uint64_t d[3] = {64, 640, 96}, s[2] = {12288, 128};     uint32_t b[3] = {64, 64, 3}; make_map(enc, &prm.wq[p], wq, 3, d, s, b); }
    { uint64_t d[3] = {64, 24576, 3}, s[2] = {384, 128};      uint32_t b[3] = {64, 96, 3}; make_map(enc, &prm.k[p],  k,  3, d, s, b); }
    { uint64_t d[3] = {64, 24576, 3}, s[2] = {384, 128};      uint32_t b[3] = {64, 96, 1}; make_map(enc, &prm.k1[p], k,  3, d, s, b); }
    { uint64_t d[3] = {64, 24576, 3}, s[2] = {384, 128};      uint32_t b[3] = {64, 96, 3}; make_map(enc, &prm.v[p],  v,  3, d, s, b); }
    { uint64_t d[3] = {64, 24576, 3}, s[2] = {384, 128};      uint32_t b[3] = {64, 96, 1}; make_map(enc, &prm.v1[p], v,  3, d, s, b); }
    prm.kptr[p] = (const uint8_t*)k; prm.vptr[p] = (const uint8_t*)v;
    prm.xptr[p] = (const uint8_t*)x; prm.wqptr[p] = (const uint8_t*)wq; prm.woptr[p] = (const uint8_t*)wo;
    { uint64_t d[2] = {640, 6144}, s[1] = {1280};             uint32_t b[2] = {64, 64};    make_map(enc, &prm.wo[p], wo, 2, d, s, b); }
  }
  { uint64_t d[2] = {6144, 1536}, s[1] = {12288};        uint32_t b[2] = {64, 16};    make_map(enc, &prm.o_st, o_ptr, 2, d, s, b); }
  { uint64_t d[2] = {6144, 1536}, s[1] = {12288};        uint32_t b[2] = {64, 96};    make_map(enc, &prm.o_ld, o_ptr, 2, d, s, b); }
  fused_attn_kernel<<<128, NTHREADS, SMEM_BYTES>>>(prm, (__nv_bfloat16*)d_out);
}
```

```cpp
#include <cuda_runtime.h>
#include <cuda_bf16.h>
#include <cuda.h>
#include <stdint.h>

namespace {

constexpr int FL_B1 = 2,  FL_B2 = 4,  FL_LD = 6;
constexpr int FL2_B1 = 3, FL2_B2 = 6, FL2_LD = 9;
constexpr int QP_L   = 2;
constexpr int TAIL_L = 3;
constexpr int PF_WIN = 10;
constexpr int PF_R0 = 0, PF_R1 = 8, PF_R2 = 11, PF_R3 = 21;

constexpr int NTHREADS   = 512;
constexpr int NSLOT      = 4;
constexpr int SLOT_BYTES = 49152;
constexpr int B_OFF      = 24576;
constexpr int KV_BYTES   = 36864;
constexpr int STG_BYTES  = 12 * 2048;
constexpr int SMEM_BYTES = NSLOT * SLOT_BYTES + STG_BYTES + 1024  ;

struct Params {
  CUtensorMap x[2], x1[2], wq[2], k[2], k1[2], v[2], v1[2], wo[2];
  CUtensorMap o_st, o_ld;
  const uint8_t* kptr[2];
  const uint8_t* vptr[2];
  const uint8_t* wqptr[2];
  uint4*    part;
  unsigned* ready;
  unsigned* xflag;
  unsigned* epoch;
};

__host__ __device__ __forceinline__ int logical_cluster(int c) {
  const unsigned tab = 0xE6CA8421u;
  int v, bp;
  if (c < 4)       { v = 0; bp = c; }
  else if (c < 36) { const int t = c - 4;  v = (tab >> (4 * (t & 7))) & 15;          bp = t >> 3; }
  else             { const int t = c - 36; v = ((tab >> (4 * (1 + t % 7))) & 15) + 1; bp = t / 7; }
  return (v >> 3) * 32 + bp * 8 + (v & 7);
}

__device__ __nv_bfloat16 g_O[1536 * 6144];
__device__ uint4         g_part[128 * 3 * 3 * 384];
__device__ unsigned      g_ready[8 * 32];
__device__ unsigned      g_xflag[128 * 12];
__device__ unsigned      g_epoch[128];

__device__ __forceinline__ uint32_t smem_u32(const void* p) { return (uint32_t)__cvta_generic_to_shared(p); }
__device__ __forceinline__ void mbar_init(uint32_t bar, uint32_t count) {
  asm volatile("mbarrier.init.shared::cta.b64 [%0], %1;" :: "r"(bar), "r"(count) : "memory");
}
__device__ __forceinline__ void mbar_expect_tx(uint32_t bar, uint32_t bytes) {
  asm volatile("mbarrier.arrive.expect_tx.shared::cta.b64 _, [%0], %1;" :: "r"(bar), "r"(bytes) : "memory");
}
__device__ __forceinline__ void mbar_arrive_both(uint32_t bar, uint32_t peer) {
  asm volatile("{\n.reg .b32 r1;\n"
               "mapa.shared::cluster.u32 r1, %1, %2;\n"
               "mbarrier.arrive.shared::cta.b64 _, [%0];\n"
               "mbarrier.arrive.shared::cluster.b64 _, [r1];\n}"
               :: "r"(bar), "r"(bar + 8 * NSLOT), "r"(peer) : "memory");
}
__device__ __forceinline__ void mbar_wait(uint32_t bar, uint32_t parity) {
  asm volatile("{\n.reg .pred P1;\n.reg .u32 cnt;\nmov.u32 cnt, 0;\n"
               "LAB_WAIT:\n"
               "mbarrier.try_wait.parity.shared::cta.b64 P1, [%0], %1;\n"
               "@P1 bra DONE;\n"
               "add.u32 cnt, cnt, 1;\n"
               "setp.lt.u32 P1, cnt, 16777216;\n"
               "@P1 bra LAB_WAIT;\n"
               "trap;\n"
               "DONE:\n}"
               :: "r"(bar), "r"(parity) : "memory");
}
__device__ __forceinline__ uint64_t policy_evict_first() {
  uint64_t p; asm volatile("createpolicy.fractional.L2::evict_first.b64 %0, 1.0;" : "=l"(p)); return p;
}
__device__ __forceinline__ void tma_2d_nohint(uint32_t dst, const CUtensorMap* m, uint32_t bar, int c0, int c1) {
  asm volatile("cp.async.bulk.tensor.2d.shared::cluster.global.mbarrier::complete_tx::bytes [%0], [%1, {%3, %4}], [%2];"
               :: "r"(dst), "l"(m), "r"(bar), "r"(c0), "r"(c1) : "memory");
}
__device__ __forceinline__ void tma_2d_mc(uint32_t dst, const CUtensorMap* m, uint32_t bar, int c0, int c1) {
  asm volatile("cp.async.bulk.tensor.2d.shared::cluster.global.mbarrier::complete_tx::bytes.multicast::cluster [%0], [%1, {%3, %4}], [%2], %5;"
               :: "r"(dst), "l"(m), "r"(bar), "r"(c0), "r"(c1), "h"((uint16_t)3) : "memory");
}
__device__ __forceinline__ void tma_2d(uint32_t dst, const CUtensorMap* m, uint32_t bar, int c0, int c1, uint64_t pol) {
  asm volatile("cp.async.bulk.tensor.2d.shared::cluster.global.mbarrier::complete_tx::bytes.L2::cache_hint [%0], [%1, {%3, %4}], [%2], %5;"
               :: "r"(dst), "l"(m), "r"(bar), "r"(c0), "r"(c1), "l"(pol) : "memory");
}
__device__ __forceinline__ void tma_3d(uint32_t dst, const CUtensorMap* m, uint32_t bar, int c0, int c1, int c2, uint64_t pol) {
  asm volatile("cp.async.bulk.tensor.3d.shared::cluster.global.mbarrier::complete_tx::bytes.L2::cache_hint [%0], [%1, {%3, %4, %5}], [%2], %6;"
               :: "r"(dst), "l"(m), "r"(bar), "r"(c0), "r"(c1), "r"(c2), "l"(pol) : "memory");
}
__device__ __forceinline__ void tma_store_2d(const CUtensorMap* m, uint32_t src, int c0, int c1) {
  asm volatile("cp.async.bulk.tensor.2d.global.shared::cta.bulk_group [%0, {%2, %3}], [%1];"
               :: "l"(m), "r"(src), "r"(c0), "r"(c1) : "memory");
}
__device__ __forceinline__ bool mbar_test(uint32_t bar, uint32_t parity) {
  uint32_t ok;
  asm volatile("{\n.reg .pred p;\nmbarrier.test_wait.parity.shared::cta.b64 p, [%1], %2;\nselp.u32 %0, 1, 0, p;\n}"
               : "=r"(ok) : "r"(bar), "r"(parity) : "memory");
  return ok;
}
__device__ __forceinline__ int lane_id() { int l; asm volatile("mov.u32 %0, %%laneid;" : "=r"(l)); return l; }
__device__ __forceinline__ void mbar_arrive(uint32_t bar) {
  asm volatile("mbarrier.arrive.shared::cta.b64 _, [%0];" :: "r"(bar) : "memory");
}
__device__ __forceinline__ void wg_fence()  { asm volatile("wgmma.fence.sync.aligned;" ::: "memory"); }
__device__ __forceinline__ void wg_commit() { asm volatile("wgmma.commit_group.sync.aligned;" ::: "memory"); }
template <int N> __device__ __forceinline__ void wg_wait() { asm volatile("wgmma.wait_group.sync.aligned %0;" :: "n"(N) : "memory"); }
__device__ __forceinline__ void tok_wait(int id) { asm volatile("bar.sync %0, 256;" :: "r"(id) : "memory"); }
__device__ __forceinline__ void tok_pass(int id) { asm volatile("bar.arrive %0, 256;" :: "r"(id) : "memory"); }
__device__ __forceinline__ void cluster_arrive_relaxed() { asm volatile("barrier.cluster.arrive.relaxed.aligned;" ::: "memory"); }
__device__ __forceinline__ void cluster_wait()           { asm volatile("barrier.cluster.wait.aligned;" ::: "memory"); }
__device__ __forceinline__ unsigned ld_relaxed(const unsigned* p) {
  unsigned v; asm volatile("ld.relaxed.gpu.global.u32 %0, [%1];" : "=r"(v) : "l"(p) : "memory"); return v;
}
__device__ __forceinline__ unsigned ld_acquire(const unsigned* p) {
  unsigned v; asm volatile("ld.acquire.gpu.global.u32 %0, [%1];" : "=r"(v) : "l"(p) : "memory"); return v;
}
__device__ __forceinline__ void red_release_add(unsigned* p, unsigned v) {
  asm volatile("red.release.gpu.global.add.u32 [%0], %1;" :: "l"(p), "r"(v) : "memory");
}
__device__ __forceinline__ void spin_until(const unsigned* p, unsigned target) {
  asm volatile("{\n.reg .pred P1;\n.reg .u32 cnt, v;\nmov.u32 cnt, 0;\n"
               "LAB_SPIN:\n"
               "ld.acquire.gpu.global.u32 v, [%0];\n"
               "sub.u32 v, v, %1;\n"
               "setp.ge.s32 P1, v, 0;\n"
               "@P1 bra DONE;\n"
               "nanosleep.u32 20;\n"
               "add.u32 cnt, cnt, 1;\n"
               "setp.lt.u32 P1, cnt, 4194304;\n"
               "@P1 bra LAB_SPIN;\n"
               "trap;\n"
               "DONE:\n}"
               :: "l"(p), "r"(target) : "memory");
}
__device__ __forceinline__ uint32_t desc_lo(uint32_t addr, uint32_t lbo) { return ((addr & 0x3FFFF) >> 4) | ((lbo >> 4) << 16); }
__device__ __forceinline__ uint64_t desc(uint32_t lo, uint32_t byte_off = 0, uint32_t hi = 0x40000040u) {
  uint64_t d;
  asm("mov.b64 %0, {%1, %2};" : "=l"(d) : "r"(lo + (byte_off >> 4)), "r"(hi));
  return d;
}
__device__ __forceinline__ uint32_t pack_bf16(float lo, float hi) {
  uint32_t r; asm("cvt.rn.bf16x2.f32 %0, %1, %2;" : "=r"(r) : "f"(hi), "f"(lo)); return r;
}
__device__ __forceinline__ float ex2(float x) { float r; asm("ex2.approx.ftz.f32 %0, %1;" : "=f"(r) : "f"(x)); return r; }

__device__ __forceinline__ void wgmma_ss_n192_tb1(float (&d)[96], uint64_t descA, uint64_t descB) {
  asm volatile("{\n.reg .pred p;\n"
    "setp.ne.b32 p, 1, 0;\n"
    "wgmma.mma_async.sync.aligned.m64n192k16.f32.bf16.bf16 "
    "{%0, %1, %2, %3, %4, %5, %6, %7, %8, %9, %10, %11, %12, %13, %14, %15, "
    "%16, %17, %18, %19, %20, %21, %22, %23, %24, %25, %26, %27, %28, %29, %30, %31, "
    "%32, %33, %34, %35, %36, %37, %38, %39, %40, %41, %42, %43, %44, %45, %46, %47, "
    "%48, %49, %50, %51, %52, %53, %54, %55, %56, %57, %58, %59, %60, %61, %62, %63, "
    "%64, %65, %66, %67, %68, %69, %70, %71, %72, %73, %74, %75, %76, %77, %78, %79, "
    "%80, %81, %82, %83, %84, %85, %86, %87, %88, %89, %90, %91, %92, %93, %94, %95}, "
    "%96, %97, p, 1, 1, 0, 1;\n}\n"
    : "+f"(d[0]), "+f"(d[1]), "+f"(d[2]), "+f"(d[3]), "+f"(d[4]), "+f"(d[5]), "+f"(d[6]), "+f"(d[7]),
      "+f"(d[8]), "+f"(d[9]), "+f"(d[10]), "+f"(d[11]), "+f"(d[12]), "+f"(d[13]), "+f"(d[14]), "+f"(d[15]),
      "+f"(d[16]), "+f"(d[17]), "+f"(d[18]), "+f"(d[19]), "+f"(d[20]), "+f"(d[21]), "+f"(d[22]), "+f"(d[23]),
      "+f"(d[24]), "+f"(d[25]), "+f"(d[26]), "+f"(d[27]), "+f"(d[28]), "+f"(d[29]), "+f"(d[30]), "+f"(d[31]),
      "+f"(d[32]), "+f"(d[33]), "+f"(d[34]), "+f"(d[35]), "+f"(d[36]), "+f"(d[37]), "+f"(d[38]), "+f"(d[39]),
      "+f"(d[40]), "+f"(d[41]), "+f"(d[42]), "+f"(d[43]), "+f"(d[44]), "+f"(d[45]), "+f"(d[46]), "+f"(d[47]),
      "+f"(d[48]), "+f"(d[49]), "+f"(d[50]), "+f"(d[51]), "+f"(d[52]), "+f"(d[53]), "+f"(d[54]), "+f"(d[55]),
      "+f"(d[56]), "+f"(d[57]), "+f"(d[58]), "+f"(d[59]), "+f"(d[60]), "+f"(d[61]), "+f"(d[62]), "+f"(d[63]),
      "+f"(d[64]), "+f"(d[65]), "+f"(d[66]), "+f"(d[67]), "+f"(d[68]), "+f"(d[69]), "+f"(d[70]), "+f"(d[71]),
      "+f"(d[72]), "+f"(d[73]), "+f"(d[74]), "+f"(d[75]), "+f"(d[76]), "+f"(d[77]), "+f"(d[78]), "+f"(d[79]),
      "+f"(d[80]), "+f"(d[81]), "+f"(d[82]), "+f"(d[83]), "+f"(d[84]), "+f"(d[85]), "+f"(d[86]), "+f"(d[87]),
      "+f"(d[88]), "+f"(d[89]), "+f"(d[90]), "+f"(d[91]), "+f"(d[92]), "+f"(d[93]), "+f"(d[94]), "+f"(d[95])
    : "l"(descA), "l"(descB));
}

__device__ __forceinline__ void wgmma_ss_n192_tb1_init(float (&d)[96], uint64_t descA, uint64_t descB) {
  asm volatile("{\n.reg .pred p;\n"
    "setp.ne.b32 p, 0, 0;\n"
    "wgmma.mma_async.sync.aligned.m64n192k16.f32.bf16.bf16 "
    "{%0, %1, %2, %3, %4, %5, %6, %7, %8, %9, %10, %11, %12, %13, %14, %15, "
    "%16, %17, %18, %19, %20, %21, %22, %23, %24, %25, %26, %27, %28, %29, %30, %31, "
    "%32, %33, %34, %35, %36, %37, %38, %39, %40, %41, %42, %43, %44, %45, %46, %47, "
    "%48, %49, %50, %51, %52, %53, %54, %55, %56, %57, %58, %59, %60, %61, %62, %63, "
    "%64, %65, %66, %67, %68, %69, %70, %71, %72, %73, %74, %75, %76, %77, %78, %79, "
    "%80, %81, %82, %83, %84, %85, %86, %87, %88, %89, %90, %91, %92, %93, %94, %95}, "
    "%96, %97, p, 1, 1, 0, 1;\n}\n"
    : "=f"(d[0]), "=f"(d[1]), "=f"(d[2]), "=f"(d[3]), "=f"(d[4]), "=f"(d[5]), "=f"(d[6]), "=f"(d[7]),
      "=f"(d[8]), "=f"(d[9]), "=f"(d[10]), "=f"(d[11]), "=f"(d[12]), "=f"(d[13]), "=f"(d[14]), "=f"(d[15]),
      "=f"(d[16]), "=f"(d[17]), "=f"(d[18]), "=f"(d[19]), "=f"(d[20]), "=f"(d[21]), "=f"(d[22]), "=f"(d[23]),
      "=f"(d[24]), "=f"(d[25]), "=f"(d[26]), "=f"(d[27]), "=f"(d[28]), "=f"(d[29]), "=f"(d[30]), "=f"(d[31]),
      "=f"(d[32]), "=f"(d[33]), "=f"(d[34]), "=f"(d[35]), "=f"(d[36]), "=f"(d[37]), "=f"(d[38]), "=f"(d[39]),
      "=f"(d[40]), "=f"(d[41]), "=f"(d[42]), "=f"(d[43]), "=f"(d[44]), "=f"(d[45]), "=f"(d[46]), "=f"(d[47]),
      "=f"(d[48]), "=f"(d[49]), "=f"(d[50]), "=f"(d[51]), "=f"(d[52]), "=f"(d[53]), "=f"(d[54]), "=f"(d[55]),
      "=f"(d[56]), "=f"(d[57]), "=f"(d[58]), "=f"(d[59]), "=f"(d[60]), "=f"(d[61]), "=f"(d[62]), "=f"(d[63]),
      "=f"(d[64]), "=f"(d[65]), "=f"(d[66]), "=f"(d[67]), "=f"(d[68]), "=f"(d[69]), "=f"(d[70]), "=f"(d[71]),
      "=f"(d[72]), "=f"(d[73]), "=f"(d[74]), "=f"(d[75]), "=f"(d[76]), "=f"(d[77]), "=f"(d[78]), "=f"(d[79]),
      "=f"(d[80]), "=f"(d[81]), "=f"(d[82]), "=f"(d[83]), "=f"(d[84]), "=f"(d[85]), "=f"(d[86]), "=f"(d[87]),
      "=f"(d[88]), "=f"(d[89]), "=f"(d[90]), "=f"(d[91]), "=f"(d[92]), "=f"(d[93]), "=f"(d[94]), "=f"(d[95])
    : "l"(descA), "l"(descB));
}

__device__ __forceinline__ void wgmma_ss_n160_tb1(float (&d)[80], uint64_t descA, uint64_t descB) {
  asm volatile("{\n.reg .pred p;\n"
    "setp.ne.b32 p, 1, 0;\n"
    "wgmma.mma_async.sync.aligned.m64n160k16.f32.bf16.bf16 "
    "{%0, %1, %2, %3, %4, %5, %6, %7, %8, %9, %10, %11, %12, %13, %14, %15, "
    "%16, %17, %18, %19, %20, %21, %22, %23, %24, %25, %26, %27, %28, %29, %30, %31, "
    "%32, %33, %34, %35, %36, %37, %38, %39, %40, %41, %42, %43, %44, %45, %46, %47, "
    "%48, %49, %50, %51, %52, %53, %54, %55, %56, %57, %58, %59, %60, %61, %62, %63, "
    "%64, %65, %66, %67, %68, %69, %70, %71, %72, %73, %74, %75, %76, %77, %78, %79}, "
    "%80, %81, p, 1, 1, 0, 1;\n}\n"
    : "+f"(d[0]), "+f"(d[1]), "+f"(d[2]), "+f"(d[3]), "+f"(d[4]), "+f"(d[5]), "+f"(d[6]), "+f"(d[7]),
      "+f"(d[8]), "+f"(d[9]), "+f"(d[10]), "+f"(d[11]), "+f"(d[12]), "+f"(d[13]), "+f"(d[14]), "+f"(d[15]),
      "+f"(d[16]), "+f"(d[17]), "+f"(d[18]), "+f"(d[19]), "+f"(d[20]), "+f"(d[21]), "+f"(d[22]), "+f"(d[23]),
      "+f"(d[24]), "+f"(d[25]), "+f"(d[26]), "+f"(d[27]), "+f"(d[28]), "+f"(d[29]), "+f"(d[30]), "+f"(d[31]),
      "+f"(d[32]), "+f"(d[33]), "+f"(d[34]), "+f"(d[35]), "+f"(d[36]), "+f"(d[37]), "+f"(d[38]), "+f"(d[39]),
      "+f"(d[40]), "+f"(d[41]), "+f"(d[42]), "+f"(d[43]), "+f"(d[44]), "+f"(d[45]), "+f"(d[46]), "+f"(d[47]),
      "+f"(d[48]), "+f"(d[49]), "+f"(d[50]), "+f"(d[51]), "+f"(d[52]), "+f"(d[53]), "+f"(d[54]), "+f"(d[55]),
      "+f"(d[56]), "+f"(d[57]), "+f"(d[58]), "+f"(d[59]), "+f"(d[60]), "+f"(d[61]), "+f"(d[62]), "+f"(d[63]),
      "+f"(d[64]), "+f"(d[65]), "+f"(d[66]), "+f"(d[67]), "+f"(d[68]), "+f"(d[69]), "+f"(d[70]), "+f"(d[71]),
      "+f"(d[72]), "+f"(d[73]), "+f"(d[74]), "+f"(d[75]), "+f"(d[76]), "+f"(d[77]), "+f"(d[78]), "+f"(d[79])
    : "l"(descA), "l"(descB));
}

__device__ __forceinline__ void wgmma_ss_n160_tb1_init(float (&d)[80], uint64_t descA, uint64_t descB) {
  asm volatile("{\n.reg .pred p;\n"
    "setp.ne.b32 p, 0, 0;\n"
    "wgmma.mma_async.sync.aligned.m64n160k16.f32.bf16.bf16 "
    "{%0, %1, %2, %3, %4, %5, %6, %7, %8, %9, %10, %11, %12, %13, %14, %15, "
    "%16, %17, %18, %19, %20, %21, %22, %23, %24, %25, %26, %27, %28, %29, %30, %31, "
    "%32, %33, %34, %35, %36, %37, %38, %39, %40, %41, %42, %43, %44, %45, %46, %47, "
    "%48, %49, %50, %51, %52, %53, %54, %55, %56, %57, %58, %59, %60, %61, %62, %63, "
    "%64, %65, %66, %67, %68, %69, %70, %71, %72, %73, %74, %75, %76, %77, %78, %79}, "
    "%80, %81, p, 1, 1, 0, 1;\n}\n"
    : "=f"(d[0]), "=f"(d[1]), "=f"(d[2]), "=f"(d[3]), "=f"(d[4]), "=f"(d[5]), "=f"(d[6]), "=f"(d[7]),
      "=f"(d[8]), "=f"(d[9]), "=f"(d[10]), "=f"(d[11]), "=f"(d[12]), "=f"(d[13]), "=f"(d[14]), "=f"(d[15]),
      "=f"(d[16]), "=f"(d[17]), "=f"(d[18]), "=f"(d[19]), "=f"(d[20]), "=f"(d[21]), "=f"(d[22]), "=f"(d[23]),
      "=f"(d[24]), "=f"(d[25]), "=f"(d[26]), "=f"(d[27]), "=f"(d[28]), "=f"(d[29]), "=f"(d[30]), "=f"(d[31]),
      "=f"(d[32]), "=f"(d[33]), "=f"(d[34]), "=f"(d[35]), "=f"(d[36]), "=f"(d[37]), "=f"(d[38]), "=f"(d[39]),
      "=f"(d[40]), "=f"(d[41]), "=f"(d[42]), "=f"(d[43]), "=f"(d[44]), "=f"(d[45]), "=f"(d[46]), "=f"(d[47]),
      "=f"(d[48]), "=f"(d[49]), "=f"(d[50]), "=f"(d[51]), "=f"(d[52]), "=f"(d[53]), "=f"(d[54]), "=f"(d[55]),
      "=f"(d[56]), "=f"(d[57]), "=f"(d[58]), "=f"(d[59]), "=f"(d[60]), "=f"(d[61]), "=f"(d[62]), "=f"(d[63]),
      "=f"(d[64]), "=f"(d[65]), "=f"(d[66]), "=f"(d[67]), "=f"(d[68]), "=f"(d[69]), "=f"(d[70]), "=f"(d[71]),
      "=f"(d[72]), "=f"(d[73]), "=f"(d[74]), "=f"(d[75]), "=f"(d[76]), "=f"(d[77]), "=f"(d[78]), "=f"(d[79])
    : "l"(descA), "l"(descB));
}

__device__ __forceinline__ void wgmma_rs_n96_tb0(float (&d)[48], uint32_t a0, uint32_t a1, uint32_t a2, uint32_t a3, uint64_t descB) {
  asm volatile("{\n.reg .pred p;\n"
    "setp.ne.b32 p, 1, 0;\n"
    "wgmma.mma_async.sync.aligned.m64n96k16.f32.bf16.bf16 "
    "{%0, %1, %2, %3, %4, %5, %6, %7, %8, %9, %10, %11, %12, %13, %14, %15, "
    "%16, %17, %18, %19, %20, %21, %22, %23, %24, %25, %26, %27, %28, %29, %30, %31, "
    "%32, %33, %34, %35, %36, %37, %38, %39, %40, %41, %42, %43, %44, %45, %46, %47}, "
    "{%48, %49, %50, %51}, %52, p, 1, 1, 0;\n}\n"
    : "+f"(d[0]), "+f"(d[1]), "+f"(d[2]), "+f"(d[3]), "+f"(d[4]), "+f"(d[5]), "+f"(d[6]), "+f"(d[7]),
      "+f"(d[8]), "+f"(d[9]), "+f"(d[10]), "+f"(d[11]), "+f"(d[12]), "+f"(d[13]), "+f"(d[14]), "+f"(d[15]),
      "+f"(d[16]), "+f"(d[17]), "+f"(d[18]), "+f"(d[19]), "+f"(d[20]), "+f"(d[21]), "+f"(d[22]), "+f"(d[23]),
      "+f"(d[24]), "+f"(d[25]), "+f"(d[26]), "+f"(d[27]), "+f"(d[28]), "+f"(d[29]), "+f"(d[30]), "+f"(d[31]),
      "+f"(d[32]), "+f"(d[33]), "+f"(d[34]), "+f"(d[35]), "+f"(d[36]), "+f"(d[37]), "+f"(d[38]), "+f"(d[39]),
      "+f"(d[40]), "+f"(d[41]), "+f"(d[42]), "+f"(d[43]), "+f"(d[44]), "+f"(d[45]), "+f"(d[46]), "+f"(d[47])
    : "r"(a0), "r"(a1), "r"(a2), "r"(a3), "l"(descB));
}

__device__ __forceinline__ void wgmma_rs_n96_tb0_init(float (&d)[48], uint32_t a0, uint32_t a1, uint32_t a2, uint32_t a3, uint64_t descB) {
  asm volatile("{\n.reg .pred p;\n"
    "setp.ne.b32 p, 0, 0;\n"
    "wgmma.mma_async.sync.aligned.m64n96k16.f32.bf16.bf16 "
    "{%0, %1, %2, %3, %4, %5, %6, %7, %8, %9, %10, %11, %12, %13, %14, %15, "
    "%16, %17, %18, %19, %20, %21, %22, %23, %24, %25, %26, %27, %28, %29, %30, %31, "
    "%32, %33, %34, %35, %36, %37, %38, %39, %40, %41, %42, %43, %44, %45, %46, %47}, "
    "{%48, %49, %50, %51}, %52, p, 1, 1, 0;\n}\n"
    : "=f"(d[0]), "=f"(d[1]), "=f"(d[2]), "=f"(d[3]), "=f"(d[4]), "=f"(d[5]), "=f"(d[6]), "=f"(d[7]),
      "=f"(d[8]), "=f"(d[9]), "=f"(d[10]), "=f"(d[11]), "=f"(d[12]), "=f"(d[13]), "=f"(d[14]), "=f"(d[15]),
      "=f"(d[16]), "=f"(d[17]), "=f"(d[18]), "=f"(d[19]), "=f"(d[20]), "=f"(d[21]), "=f"(d[22]), "=f"(d[23]),
      "=f"(d[24]), "=f"(d[25]), "=f"(d[26]), "=f"(d[27]), "=f"(d[28]), "=f"(d[29]), "=f"(d[30]), "=f"(d[31]),
      "=f"(d[32]), "=f"(d[33]), "=f"(d[34]), "=f"(d[35]), "=f"(d[36]), "=f"(d[37]), "=f"(d[38]), "=f"(d[39]),
      "=f"(d[40]), "=f"(d[41]), "=f"(d[42]), "=f"(d[43]), "=f"(d[44]), "=f"(d[45]), "=f"(d[46]), "=f"(d[47])
    : "r"(a0), "r"(a1), "r"(a2), "r"(a3), "l"(descB));
}

__device__ __forceinline__ void wgmma_rs_n128_tb1(float (&d)[64], uint32_t a0, uint32_t a1, uint32_t a2, uint32_t a3, uint64_t descB) {
  asm volatile("{\n.reg .pred p;\n"
    "setp.ne.b32 p, 1, 0;\n"
    "wgmma.mma_async.sync.aligned.m64n128k16.f32.bf16.bf16 "
    "{%0, %1, %2, %3, %4, %5, %6, %7, %8, %9, %10, %11, %12, %13, %14, %15, "
    "%16, %17, %18, %19, %20, %21, %22, %23, %24, %25, %26, %27, %28, %29, %30, %31, "
    "%32, %33, %34, %35, %36, %37, %38, %39, %40, %41, %42, %43, %44, %45, %46, %47, "
    "%48, %49, %50, %51, %52, %53, %54, %55, %56, %57, %58, %59, %60, %61, %62, %63}, "
    "{%64, %65, %66, %67}, %68, p, 1, 1, 1;\n}\n"
    : "+f"(d[0]), "+f"(d[1]), "+f"(d[2]), "+f"(d[3]), "+f"(d[4]), "+f"(d[5]), "+f"(d[6]), "+f"(d[7]),
      "+f"(d[8]), "+f"(d[9]), "+f"(d[10]), "+f"(d[11]), "+f"(d[12]), "+f"(d[13]), "+f"(d[14]), "+f"(d[15]),
      "+f"(d[16]), "+f"(d[17]), "+f"(d[18]), "+f"(d[19]), "+f"(d[20]), "+f"(d[21]), "+f"(d[22]), "+f"(d[23]),
      "+f"(d[24]), "+f"(d[25]), "+f"(d[26]), "+f"(d[27]), "+f"(d[28]), "+f"(d[29]), "+f"(d[30]), "+f"(d[31]),
      "+f"(d[32]), "+f"(d[33]), "+f"(d[34]), "+f"(d[35]), "+f"(d[36]), "+f"(d[37]), "+f"(d[38]), "+f"(d[39]),
      "+f"(d[40]), "+f"(d[41]), "+f"(d[42]), "+f"(d[43]), "+f"(d[44]), "+f"(d[45]), "+f"(d[46]), "+f"(d[47]),
      "+f"(d[48]), "+f"(d[49]), "+f"(d[50]), "+f"(d[51]), "+f"(d[52]), "+f"(d[53]), "+f"(d[54]), "+f"(d[55]),
      "+f"(d[56]), "+f"(d[57]), "+f"(d[58]), "+f"(d[59]), "+f"(d[60]), "+f"(d[61]), "+f"(d[62]), "+f"(d[63])
    : "r"(a0), "r"(a1), "r"(a2), "r"(a3), "l"(descB));
}

__device__ __forceinline__ void wgmma_rs_n128_tb1_init(float (&d)[64], uint32_t a0, uint32_t a1, uint32_t a2, uint32_t a3, uint64_t descB) {
  asm volatile("{\n.reg .pred p;\n"
    "setp.ne.b32 p, 0, 0;\n"
    "wgmma.mma_async.sync.aligned.m64n128k16.f32.bf16.bf16 "
    "{%0, %1, %2, %3, %4, %5, %6, %7, %8, %9, %10, %11, %12, %13, %14, %15, "
    "%16, %17, %18, %19, %20, %21, %22, %23, %24, %25, %26, %27, %28, %29, %30, %31, "
    "%32, %33, %34, %35, %36, %37, %38, %39, %40, %41, %42, %43, %44, %45, %46, %47, "
    "%48, %49, %50, %51, %52, %53, %54, %55, %56, %57, %58, %59, %60, %61, %62, %63}, "
    "{%64, %65, %66, %67}, %68, p, 1, 1, 1;\n}\n"
    : "=f"(d[0]), "=f"(d[1]), "=f"(d[2]), "=f"(d[3]), "=f"(d[4]), "=f"(d[5]), "=f"(d[6]), "=f"(d[7]),
      "=f"(d[8]), "=f"(d[9]), "=f"(d[10]), "=f"(d[11]), "=f"(d[12]), "=f"(d[13]), "=f"(d[14]), "=f"(d[15]),
      "=f"(d[16]), "=f"(d[17]), "=f"(d[18]), "=f"(d[19]), "=f"(d[20]), "=f"(d[21]), "=f"(d[22]), "=f"(d[23]),
      "=f"(d[24]), "=f"(d[25]), "=f"(d[26]), "=f"(d[27]), "=f"(d[28]), "=f"(d[29]), "=f"(d[30]), "=f"(d[31]),
      "=f"(d[32]), "=f"(d[33]), "=f"(d[34]), "=f"(d[35]), "=f"(d[36]), "=f"(d[37]), "=f"(d[38]), "=f"(d[39]),
      "=f"(d[40]), "=f"(d[41]), "=f"(d[42]), "=f"(d[43]), "=f"(d[44]), "=f"(d[45]), "=f"(d[46]), "=f"(d[47]),
      "=f"(d[48]), "=f"(d[49]), "=f"(d[50]), "=f"(d[51]), "=f"(d[52]), "=f"(d[53]), "=f"(d[54]), "=f"(d[55]),
      "=f"(d[56]), "=f"(d[57]), "=f"(d[58]), "=f"(d[59]), "=f"(d[60]), "=f"(d[61]), "=f"(d[62]), "=f"(d[63])
    : "r"(a0), "r"(a1), "r"(a2), "r"(a3), "l"(descB));
}

__device__ __forceinline__ void wgmma_rs_n64_tb1(float (&d)[32], uint32_t a0, uint32_t a1, uint32_t a2, uint32_t a3, uint64_t descB) {
  asm volatile("{\n.reg .pred p;\n"
    "setp.ne.b32 p, 1, 0;\n"
    "wgmma.mma_async.sync.aligned.m64n64k16.f32.bf16.bf16 "
    "{%0, %1, %2, %3, %4, %5, %6, %7, %8, %9, %10, %11, %12, %13, %14, %15, "
    "%16, %17, %18, %19, %20, %21, %22, %23, %24, %25, %26, %27, %28, %29, %30, %31}, "
    "{%32, %33, %34, %35}, %36, p, 1, 1, 1;\n}\n"
    : "+f"(d[0]), "+f"(d[1]), "+f"(d[2]), "+f"(d[3]), "+f"(d[4]), "+f"(d[5]), "+f"(d[6]), "+f"(d[7]),
      "+f"(d[8]), "+f"(d[9]), "+f"(d[10]), "+f"(d[11]), "+f"(d[12]), "+f"(d[13]), "+f"(d[14]), "+f"(d[15]),
      "+f"(d[16]), "+f"(d[17]), "+f"(d[18]), "+f"(d[19]), "+f"(d[20]), "+f"(d[21]), "+f"(d[22]), "+f"(d[23]),
      "+f"(d[24]), "+f"(d[25]), "+f"(d[26]), "+f"(d[27]), "+f"(d[28]), "+f"(d[29]), "+f"(d[30]), "+f"(d[31])
    : "r"(a0), "r"(a1), "r"(a2), "r"(a3), "l"(descB));
}

__device__ __forceinline__ void wgmma_rs_n64_tb1_init(float (&d)[32], uint32_t a0, uint32_t a1, uint32_t a2, uint32_t a3, uint64_t descB) {
  asm volatile("{\n.reg .pred p;\n"
    "setp.ne.b32 p, 0, 0;\n"
    "wgmma.mma_async.sync.aligned.m64n64k16.f32.bf16.bf16 "
    "{%0, %1, %2, %3, %4, %5, %6, %7, %8, %9, %10, %11, %12, %13, %14, %15, "
    "%16, %17, %18, %19, %20, %21, %22, %23, %24, %25, %26, %27, %28, %29, %30, %31}, "
    "{%32, %33, %34, %35}, %36, p, 1, 1, 1;\n}\n"
    : "=f"(d[0]), "=f"(d[1]), "=f"(d[2]), "=f"(d[3]), "=f"(d[4]), "=f"(d[5]), "=f"(d[6]), "=f"(d[7]),
      "=f"(d[8]), "=f"(d[9]), "=f"(d[10]), "=f"(d[11]), "=f"(d[12]), "=f"(d[13]), "=f"(d[14]), "=f"(d[15]),
      "=f"(d[16]), "=f"(d[17]), "=f"(d[18]), "=f"(d[19]), "=f"(d[20]), "=f"(d[21]), "=f"(d[22]), "=f"(d[23]),
      "=f"(d[24]), "=f"(d[25]), "=f"(d[26]), "=f"(d[27]), "=f"(d[28]), "=f"(d[29]), "=f"(d[30]), "=f"(d[31])
    : "r"(a0), "r"(a1), "r"(a2), "r"(a3), "l"(descB));
}

template <int V> struct Int { static constexpr int value = V; };

struct Ring {
  uint32_t u;
  __device__ __forceinline__ uint32_t slot()  const { return u & (NSLOT - 1); }
  __device__ __forceinline__ uint32_t phase() const { return (u >> 2) & 1; }
  __device__ __forceinline__ uint32_t full(uint32_t full0)   const { return full0 + 8 * slot(); }
  __device__ __forceinline__ uint32_t empty(uint32_t full0)  const { return full0 + 8 * NSLOT + 8 * slot(); }
  __device__ __forceinline__ uint32_t addr(uint32_t ring)    const { return ring + slot() * SLOT_BYTES; }
  __device__ __forceinline__ Ring operator+(uint32_t d) const { return Ring{u + d}; }
};

__device__ __forceinline__ void softmax96(float (&s)[48], uint32_t (&p)[24], float& r0, float& r1) {
  const float c = 0.07216878364870322f * 1.4426950408889634f;
  float a0[6], a1[6];
#pragma unroll
  for (int j = 0; j < 6; j++) {
    a0[j] = fmaxf(fmaxf(s[8 * j], s[8 * j + 1]), fmaxf(s[8 * j + 4], s[8 * j + 5]));
    a1[j] = fmaxf(fmaxf(s[8 * j + 2], s[8 * j + 3]), fmaxf(s[8 * j + 6], s[8 * j + 7]));
  }
  float m0 = fmaxf(fmaxf(fmaxf(a0[0], a0[1]), fmaxf(a0[2], a0[3])), fmaxf(a0[4], a0[5]));
  float m1 = fmaxf(fmaxf(fmaxf(a1[0], a1[1]), fmaxf(a1[2], a1[3])), fmaxf(a1[4], a1[5]));
  m0 = fmaxf(m0, __shfl_xor_sync(0xffffffffu, m0, 1));
  m1 = fmaxf(m1, __shfl_xor_sync(0xffffffffu, m1, 1));
  m0 = fmaxf(m0, __shfl_xor_sync(0xffffffffu, m0, 2));
  m1 = fmaxf(m1, __shfl_xor_sync(0xffffffffu, m1, 2));
  const float b0 = -m0 * c, b1 = -m1 * c;
  float l0 = 0.f, l1 = 0.f;
#pragma unroll
  for (int j = 0; j < 12; j++) {
    const float e0 = ex2(fmaf(s[4 * j],     c, b0)), e1 = ex2(fmaf(s[4 * j + 1], c, b0));
    const float e2 = ex2(fmaf(s[4 * j + 2], c, b1)), e3 = ex2(fmaf(s[4 * j + 3], c, b1));
    l0 += e0 + e1;
    l1 += e2 + e3;
    p[2 * j]     = pack_bf16(e0, e1);
    p[2 * j + 1] = pack_bf16(e2, e3);
  }
  l0 += __shfl_xor_sync(0xffffffffu, l0, 1);
  l1 += __shfl_xor_sync(0xffffffffu, l1, 1);
  l0 += __shfl_xor_sync(0xffffffffu, l0, 2);
  l1 += __shfl_xor_sync(0xffffffffu, l1, 2);
  asm("rcp.approx.ftz.f32 %0, %1;" : "=f"(r0) : "f"(l0));
  asm("rcp.approx.ftz.f32 %0, %1;" : "=f"(r1) : "f"(l1));
}

template <bool INIT>
__device__ __forceinline__ void qk_mma(float (&s)[48], const uint32_t (&qf)[48], uint32_t box0, uint32_t box1, uint32_t box2, int pass_id) {
  const uint32_t d0 = desc_lo(box0, 16), d1 = desc_lo(box1, 16), d2 = desc_lo(box2, 16);
  if (INIT) wgmma_rs_n96_tb0_init(s, qf[0], qf[1], qf[2], qf[3], desc(d0));
  else      wgmma_rs_n96_tb0(s, qf[0], qf[1], qf[2], qf[3], desc(d0));
#pragma unroll
  for (int k = 1; k < 12; k++) {
    wgmma_rs_n96_tb0(s, qf[4 * k], qf[4 * k + 1], qf[4 * k + 2], qf[4 * k + 3], desc(k < 4 ? d0 : k < 8 ? d1 : d2, (k & 3) * 32));
  }
  tok_pass(pass_id);
}
template <bool INIT>
__device__ __forceinline__ void pv_mma(float (&o)[96], const uint32_t (&pf)[24], uint32_t box01, uint32_t box2, int pass_id) {
  float (&oa)[64] = *reinterpret_cast<float (*)[64]>(&o[0]);
  float (&ob)[32] = *reinterpret_cast<float (*)[32]>(&o[64]);
  const uint32_t da = desc_lo(box01, 12288), db = desc_lo(box2, 12288);
  if (INIT) { wgmma_rs_n128_tb1_init(oa, pf[0], pf[1], pf[2], pf[3], desc(da)); wgmma_rs_n64_tb1_init(ob, pf[0], pf[1], pf[2], pf[3], desc(db)); }
  else      { wgmma_rs_n128_tb1(oa, pf[0], pf[1], pf[2], pf[3], desc(da));      wgmma_rs_n64_tb1(ob, pf[0], pf[1], pf[2], pf[3], desc(db)); }
#pragma unroll
  for (int k = 1; k < 6; k++) {
    wgmma_rs_n128_tb1(oa, pf[4 * k], pf[4 * k + 1], pf[4 * k + 2], pf[4 * k + 3], desc(da, k * 2048));
    wgmma_rs_n64_tb1(ob, pf[4 * k], pf[4 * k + 1], pf[4 * k + 2], pf[4 * k + 3], desc(db, k * 2048));
  }
  tok_pass(pass_id);
}

__global__ void __cluster_dims__(2, 1, 1) __launch_bounds__(NTHREADS, 1)
fused_attn_kernel(const __grid_constant__ Params prm, __nv_bfloat16* __restrict__ out) {
  extern __shared__ uint8_t smem_raw[];
  __shared__ uint64_t s_bars[3 * NSLOT + 10];
  __shared__ uint32_t s_dummy[64];
  __shared__ volatile uint32_t s_prog;

  const uint32_t ring = (smem_u32(smem_raw) + 1023) & ~1023u;
  const uint32_t stg  = ring + NSLOT * SLOT_BYTES;
  const uint32_t full0 = smem_u32(&s_bars[0]);
  const uint32_t o_done  = full0 + 24 * NSLOT;
  const uint32_t o_ready = o_done + 48;

  const int tid = threadIdx.x, lane = tid & 31;
  const int warp = __shfl_sync(0xffffffffu, tid >> 5, 0);
  const int rank = blockIdx.x & 1, cl = logical_cluster(blockIdx.x >> 1), cta = 2 * cl + rank;
  const int grp = cl >> 3, prob = grp >> 2, bp = grp & 3, j8 = cl & 7;
  const int split = j8 >> 1;

  if (tid == 13 * 32) {
    asm volatile("prefetch.tensormap [%0];" :: "l"(&prm.wq[prob]) : "memory");
    asm volatile("prefetch.tensormap [%0];" :: "l"(&prm.x1[prob]) : "memory");
    asm volatile("prefetch.tensormap [%0];" :: "l"(&prm.x[prob]) : "memory");
  }
  if (tid == 12 * 32) {
#pragma unroll
    for (int s = 0; s < NSLOT; s++) { mbar_init(full0 + 8 * s, 1); mbar_init(full0 + 8 * NSLOT + 8 * s, 3); mbar_init(full0 + 16 * NSLOT + 8 * s, 3); }
    for (int s = 0; s < 6; s++) mbar_init(o_done + 8 * s, 12);
    for (int s = 0; s < 4; s++) mbar_init(o_ready + 8 * s, 1);
    s_prog = NSLOT;
    asm volatile("fence.mbarrier_init.release.cluster;" ::: "memory");
  }
  __syncthreads();
  cluster_arrive_relaxed();
  if (tid == 12 * 32) {
    const int h = 2 * j8 + rank;
    const uint64_t pol = policy_evict_first();
#pragma unroll
    for (int s = 0; s < NSLOT; s++) {
      mbar_expect_tx(full0 + 8 * s, SLOT_BYTES);
      tma_2d_nohint(ring + s * SLOT_BYTES, &prm.x1[prob], full0 + 8 * s, 64 * s, 192 * bp);
      tma_3d(ring + s * SLOT_BYTES + B_OFF, &prm.wq[prob], full0 + 8 * s, 0, 64 * s, 3 * h, pol);
    }
  }
  __syncwarp();
  cluster_wait();

  if (warp >= 12) {
    asm volatile("setmaxnreg.dec.sync.aligned.u32 32;");
    if (warp == 12) {
      if (lane == 0) {
        Ring r{0};
        const uint64_t pol_s = policy_evict_first();
        const int ncol0 = 320 * (j8 & 1);
#pragma unroll 1
        for (int w = 0; w < 2; w++) {
          const int h = 16 * w + 2 * j8 + rank;
#pragma unroll 1
          for (int ks = 0; ks < 10; ks++) {
            const uint32_t fb = r.full(full0), sl = r.addr(ring);
            if (r.u >= NSLOT) {
              mbar_wait(r.empty(full0), r.phase() ^ 1);
              mbar_expect_tx(fb, SLOT_BYTES);
              s_prog = r.u;
              tma_3d(sl + B_OFF, &prm.wq[prob], fb, 0, 64 * ks, 3 * h, pol_s);
              mbar_wait(r.empty(full0) + 8 * NSLOT, r.phase() ^ 1);
              tma_2d_mc(sl + rank * 12288, &prm.x[prob], fb, 64 * ks, 192 * bp + 96 * rank);
            }
            r.u++;
          }
#pragma unroll 1
          for (int t = 0; t < 3; t++) {
            const uint32_t fb = r.full(full0), sl = r.addr(ring);
            const int row0 = ((2 * bp) * 32 + h) * 96, row1 = row0 + 32 * 96;
            mbar_wait(r.empty(full0), r.phase() ^ 1);
            mbar_expect_tx(fb, SLOT_BYTES);
            s_prog = r.u;
            if (t == 0) {
              tma_3d(sl,         &prm.k[prob],  fb, 0, row0, 0, pol_s);
              tma_3d(sl + 36864, &prm.k1[prob], fb, 0, row1, 0, pol_s);
            } else if (t == 1) {
              tma_3d(sl,         &prm.k1[prob], fb, 0, row1, 1, pol_s);
              tma_3d(sl + 12288, &prm.k1[prob], fb, 0, row1, 2, pol_s);
              tma_3d(sl + 24576, &prm.v1[prob], fb, 0, row0, 0, pol_s);
              tma_3d(sl + 36864, &prm.v1[prob], fb, 0, row0, 1, pol_s);
            } else {
              tma_3d(sl,         &prm.v1[prob], fb, 0, row0, 2, pol_s);
              tma_3d(sl + 12288, &prm.v[prob],  fb, 0, row1, 0, pol_s);
            }
            mbar_wait(r.empty(full0) + 8 * NSLOT, r.phase() ^ 1);
            r.u++;
          }
        }
#pragma unroll 1
        for (int i = 0; i < 24; i++) {
          const int h = i < 12 ? 4 * split + i / 3 : 16 + 4 * split + (i & 3);
          const int c = i < 12 ? i % 3 : (i - 12) >> 2;
          const uint32_t fb = r.full(full0), sl = r.addr(ring);
          const int k0 = h * 192 + c * 64;
          mbar_wait(r.empty(full0), r.phase() ^ 1);
          mbar_expect_tx(fb, SLOT_BYTES);
          s_prog = r.u;
          tma_2d(sl + B_OFF,         &prm.wo[prob],   fb, ncol0 + 192 * rank,      k0, pol_s);
          tma_2d(sl + B_OFF + 8192,  &prm.wo[prob],   fb, ncol0 + 192 * rank + 64, k0, pol_s);
          tma_2d(sl + B_OFF + 16384, &prm.wo[prob],   fb, ncol0 + 128, k0, pol_s);
          if (i == 0 || (i >= 12 && (i & 3) == 0)) {
            mbar_wait(o_ready + 8 * (i == 0 ? 0 : (i >> 2) - 2), 0);
          }
          mbar_wait(r.empty(full0) + 8 * NSLOT, r.phase() ^ 1);
          tma_2d_mc(sl + rank * 12288, &prm.o_ld, fb, k0, prob * 768 + 192 * bp + 96 * rank);
          r.u++;
        }
      }
    } else if (warp == 13) {
      {
        const unsigned obase = 3u * ld_relaxed(&prm.epoch[cta]);
        uint32_t pub = 0, wat = 0;
#pragma unroll 1
        for (int it = 0; it < (1 << 22) && (pub < 6 || wat < 4); it++) {
          if (pub < 6 && mbar_test(o_done + 8 * pub, 0)) {
            uint32_t n = 1;
            while ((pub + n) % 3 != 0 && mbar_test(o_done + 8 * (pub + n), 0)) n++;
            if (lane == 0) {
              red_release_add(&prm.ready[grp * 32 + 16 * (pub >= 3) + 2 * j8 + rank], n);
            }
            __syncwarp();
            pub += n;
          } else if (wat < 4 && pub > wat + 2) {
            const unsigned tgt = obase + (wat == 0 ? 3u : wat);
            const unsigned a = ld_acquire(&prm.ready[grp * 32 + (wat == 0 ? 0 : 16) + 4 * split + (lane & 3)]);
            if (__all_sync(0xffffffffu, (int)(a - tgt) >= 0)) {
              if (lane == 0) {
                asm volatile("fence.proxy.async;" ::: "memory");
                mbar_arrive(o_ready + 8 * wat);
              }
              __syncwarp();
              wat++;
            }
          } else {
            mbar_wait(o_done + 8 * pub, 0);
          }
        }
      }
    } else {
      const int h0 = 2 * j8 + rank;
      const uint8_t* wqp = prm.wqptr[prob];
      auto addr_of = [&](int n) -> const uint8_t* {
        if (n < 9 || (n >= 45 && n < 60)) {
          const bool second = n >= 45;
          const int i = (second ? n - 45 : n + 6) * 32 + lane;
          const int ks = i / 48, rem = i - ks * 48;
          return wqp + (size_t)(64 * ks + 16 * bp + rem / 3) * 12288 + (h0 + (second ? 16 : 0)) * 384 + (rem % 3) * 128;
        }
        const bool second = n >= 60;
        const int m = second ? n - 60 : n - 9, tile = m / 9;
        const uint8_t* base = (tile < 2) ? prm.kptr[prob] : prm.vptr[prob];
        return base + (size_t)((2 * bp + (tile & 1)) * 32 + h0 + (second ? 16 : 0)) * KV_BYTES + (m - 9 * tile) * 4096 + lane * 128;
      };
      auto use_of = [&](int n) -> int {
        if (n < 9)  return ((n + 6) * 32) / 48;
        if (n < 45) { const int t = (n - 9) / 9; return 10 + (t < 2 ? 0 : t - 1); }
        if (n < 60) return 13 + ((n - 45) * 32) / 48;
        const int t = (n - 60) / 9;
        return 23 + (t < 2 ? 0 : t - 1);
      };
      auto release_of = [&](int n) -> int {
        if (n < 9)  return 0;
        if (n < 45) return PF_R0 + ((n - 9) * (PF_R1 - PF_R0)) / 36;
        if (n < 60) return PF_R1 + ((n - 45) * (PF_R2 - PF_R1)) / 15;
        return PF_R2 + ((n - 60) * (PF_R3 - PF_R2)) / 36;
      };
      const uint32_t dummy = smem_u32(&s_dummy[tid & 63]);
#pragma unroll 1
      for (int n = warp - 14; n < 96; n += 2) {
        const int u = use_of(n), rel = release_of(n);
        int guard = 0;
        while ((int)s_prog < rel && ++guard < (1 << 20)) __nanosleep(100);
        if ((int)s_prog < u)
          asm volatile("cp.async.ca.shared.global.L2::128B [%0], [%1], 4;" :: "r"(dummy), "l"(addr_of(n)) : "memory");
        asm volatile("cp.async.commit_group;" ::: "memory");
        asm volatile("cp.async.wait_group %0;" :: "n"(PF_WIN) : "memory");
      }
      asm volatile("cp.async.wait_group 0;" ::: "memory");
    }
  } else {
    asm volatile("setmaxnreg.inc.sync.aligned.u32 160;");
    const int wg = warp >> 2, wq4 = warp & 3;
    const bool elected = wq4 == 0 && lane_id() == 0;
    const uint32_t descA0 = desc_lo(ring + wg * 8192, 16), descB0 = desc_lo(ring + B_OFF, 8192);
    Ring r{0};
    uint32_t pend[32];
    const uint32_t wstg = stg + warp * 2048;
    auto stg_acquire = [&]() {
      if (lane_id() == 0) asm volatile("cp.async.bulk.wait_group.read 0;" ::: "memory");
      __syncwarp();
    };
    auto stage_in = [&](const uint32_t* v) {
      stg_acquire();
      const int lane = lane_id(), r8 = lane & 7;
      const uint32_t st_base = wstg + (((lane >> 3) & 1) * 8 + r8) * 128;
#pragma unroll
      for (int jj = 0; jj < 4; jj++) {
        const uint32_t addr = st_base + (((2 * jj + (lane >> 4)) ^ r8) << 4);
        asm volatile("stmatrix.sync.aligned.m8n8.x4.shared.b16 [%0], {%1, %2, %3, %4};"
                     :: "r"(addr), "r"(v[4 * jj]), "r"(v[4 * jj + 1]), "r"(v[4 * jj + 2]), "r"(v[4 * jj + 3]) : "memory");
      }
    };
    auto send = [&](int wv, int box) {
      asm volatile("fence.proxy.async.shared::cta;" ::: "memory");
      __syncwarp();
      if (lane_id() == 0) {
        tma_store_2d(&prm.o_st, wstg, (16 * wv + 2 * j8 + rank) * 192 + 64 * box, prob * 768 + 192 * bp + 16 * warp);
        asm volatile("cp.async.bulk.commit_group;" ::: "memory");
      }
    };
    auto landed = [&](int ev, auto pending) {
      if (lane_id() == 0) {
        asm volatile("cp.async.bulk.wait_group %0;" :: "n"(decltype(pending)::value) : "memory");
        mbar_arrive(o_done + 8 * ev);
      }
    };

#pragma unroll 1
    for (int w = 0; w < 2; w++) {
      uint32_t qf[48];
      {
        float acc[96];
        {
          const uint32_t da = descA0 + r.slot() * (SLOT_BYTES >> 4), db = descB0 + r.slot() * (SLOT_BYTES >> 4);
          mbar_wait(r.full(full0), r.phase());
          if (w > 0) { if (wg == 0) tok_wait(14); else if (wg == 2) tok_wait(15); }
          wg_fence();
          wgmma_ss_n192_tb1_init(acc, desc(da), desc(db));
#pragma unroll
          for (int k = 1; k < 4; k++) wgmma_ss_n192_tb1(acc, desc(da, k * 32), desc(db, k * 2048));
          wg_commit();
          if (w > 0 && wg == 0) tok_pass(15);
          if (w > 0) send(0, 0);
          r.u++;
        }
#pragma unroll 1
        for (int ks = 1; ks < 10; ks++) {
          const uint32_t da = descA0 + r.slot() * (SLOT_BYTES >> 4), db = descB0 + r.slot() * (SLOT_BYTES >> 4);
          mbar_wait(r.full(full0), r.phase());
          const bool parked = ks == 10 - QP_L && wg != 1;
          if (parked) {
            if (QP_L > 1) { wg_wait<0>(); if (elected) mbar_arrive_both(Ring{r.u - 1}.empty(full0), rank ^ 1); }
            tok_wait(wg == 0 ? 4 : 5);
          }
          wg_fence();
          wgmma_ss_n192_tb1(acc, desc(da), desc(db));
          wg_commit();
          wg_wait<1>();
          if (!(parked && QP_L > 1) && elected) mbar_arrive_both(Ring{r.u - 1}.empty(full0), rank ^ 1);
#pragma unroll
          for (int k = 1; k < 4; k++) wgmma_ss_n192_tb1(acc, desc(da, k * 32), desc(db, k * 2048));
          wg_commit();
          if (ks == 9 && wg != 2) tok_pass(wg == 1 ? 4 : 5);
          if (w > 0) {
            if (ks == FL_B1)      { stage_in(pend);      send(0, 1); }
            else if (ks == FL_B2) { stage_in(pend + 16); send(0, 2); }
            else if (ks == FL_LD) { landed(0, Int<0>{}); landed(1, Int<0>{}); landed(2, Int<0>{}); }
          }
          r.u++;
        }
        mbar_wait(r.full(full0), r.phase());
        if (wg == 2) mbar_wait((r + 1).full(full0), (r + 1).phase());
        wg_wait<0>();
        if (elected) mbar_arrive_both(Ring{r.u - 1}.empty(full0), rank ^ 1);
        stg_acquire();
        const int lane = lane_id();
#pragma unroll
        for (int i = 0; i < 4; i++)
          asm volatile("st.shared.v4.u32 [%0], {%1, %2, %3, %4};"
                       :: "r"(wstg + i * 512 + lane * 16),
                          "r"(pack_bf16(acc[64 + 8 * i], acc[65 + 8 * i])), "r"(pack_bf16(acc[66 + 8 * i], acc[67 + 8 * i])),
                          "r"(pack_bf16(acc[68 + 8 * i], acc[69 + 8 * i])), "r"(pack_bf16(acc[70 + 8 * i], acc[71 + 8 * i])) : "memory");
#pragma unroll
        for (int i = 0; i < 32; i++) qf[i] = pack_bf16(acc[2 * i], acc[2 * i + 1]);
        asm volatile("" ::: "memory");
#pragma unroll
        for (int i = 0; i < 4; i++)
          asm volatile("ld.shared.v4.u32 {%0, %1, %2, %3}, [%4];"
                       : "=r"(qf[32 + 4 * i]), "=r"(qf[33 + 4 * i]), "=r"(qf[34 + 4 * i]), "=r"(qf[35 + 4 * i])
                       : "r"(wstg + i * 512 + lane * 16) : "memory");
      }
      const Ring rX = r, rY = r + 1, rZ = r + 2;
      r.u += 3;
      uint32_t pf[24];
      float rinv0, rinv1;
      bool z_ready;
      const uint32_t aX = rX.addr(ring), aY = rY.addr(ring), aZ = rZ.addr(ring);
      {
        float s[48];
        if (wg != 1) tok_wait(wg == 0 ? 7 : 9);
        wg_fence();
        qk_mma<true>(s, qf, wg == 2 ? aX + 36864 : aX, wg == 2 ? aY : aX + 12288, wg == 2 ? aY + 12288 : aX + 24576, wg == 1 ? 7 : wg == 0 ? 8 : 10);
        wg_commit();
        if (wg != 2) mbar_wait(rY.full(full0), rY.phase());
        wg_wait<0>();
        if (wg == 1) {
          if (wq4 < 2) {
#pragma unroll
            for (int i = 0; i < 48; i++) qf[i] = 0u;
          } else {
#pragma unroll
            for (int i = 0; i < 48; i++) s[i] = 0.f;
          }
          tok_wait(8);
          wg_fence();
          qk_mma<false>(s, qf, aX + 36864, aY, aY + 12288, 9);
          wg_commit();
          wg_wait<0>();
        }
        if (elected) { mbar_arrive_both(rX.empty(full0), rank ^ 1); if (wg == 2) mbar_arrive_both(rY.empty(full0), rank ^ 1); }
        __syncwarp();
        z_ready = mbar_test(rZ.full(full0), rZ.phase());
        softmax96(s, pf, rinv0, rinv1);
      }
      float o[96];
      {
        if (!__all_sync(0xffffffffu, z_ready)) mbar_wait(rZ.full(full0), rZ.phase());
        tok_wait(wg == 0 ? 10 : wg == 1 ? 11 : 12);
        wg_fence();
        pv_mma<true>(o, pf, wg == 2 ? aZ + 12288 : aY + 24576, wg == 2 ? aZ + 36864 : aZ, wg == 0 ? 11 : wg == 1 ? 12 : 13);
        wg_commit();
        wg_wait<0>();
        if (wg == 1) {
          if (elected) mbar_arrive_both(rY.empty(full0), rank ^ 1);
          if (wq4 < 2) {
#pragma unroll
            for (int i = 0; i < 24; i++) pf[i] = 0u;
          } else {
#pragma unroll
            for (int i = 0; i < 96; i++) o[i] = 0.f;
          }
          tok_wait(13);
          wg_fence();
          pv_mma<false>(o, pf, aZ + 12288, aZ + 36864, 14);
          wg_commit();
          wg_wait<0>();
        }
        if (elected) { if (wg == 0) mbar_arrive_both(rY.empty(full0), rank ^ 1); mbar_arrive_both(rZ.empty(full0), rank ^ 1); }
      }
      {
        uint32_t v[16];
#pragma unroll
        for (int i = 0; i < 16; i++) { const float ri = (i & 1) ? rinv1 : rinv0; v[i] = pack_bf16(o[2 * i] * ri, o[2 * i + 1] * ri); }
#pragma unroll
        for (int i = 0; i < 32; i++) { const float ri = (i & 1) ? rinv1 : rinv0; pend[i] = pack_bf16(o[32 + 2 * i] * ri, o[33 + 2 * i] * ri); }
        stage_in(v);
      }
    }

    const unsigned otarget = ld_relaxed(&prm.epoch[cta]) + 1u, target = 3u * otarget;
    const uint32_t bhi = 0x40000040u | (rank ? 4u << 17 : 0u);
    float acc[80];
    {
      {
        const uint32_t da = descA0 + r.slot() * (SLOT_BYTES >> 4), db = descB0 + r.slot() * (SLOT_BYTES >> 4);
        mbar_wait(r.full(full0), r.phase());
        if (wg == 0) tok_wait(14); else if (wg == 2) tok_wait(15);
        wg_fence();
        wgmma_ss_n160_tb1_init(acc, desc(da), desc(db, 0, bhi));
#pragma unroll
        for (int k = 1; k < 4; k++) wgmma_ss_n160_tb1(acc, desc(da, k * 32), desc(db, k * 2048, bhi));
        wg_commit();
        if (wg == 0) tok_pass(15);
        send(1, 0);
        r.u++;
      }
#pragma unroll 1
      for (int ks = 1; ks < 24; ks++) {
        const uint32_t da = descA0 + r.slot() * (SLOT_BYTES >> 4), db = descB0 + r.slot() * (SLOT_BYTES >> 4);
        const bool parked = TAIL_L > 0 && ks == 24 - TAIL_L && wg > 0;
        if (parked) {
          wg_wait<0>();
          if (ks <= 24 - NSLOT && elected) mbar_arrive_both(Ring{r.u - 1}.empty(full0), rank ^ 1);
          tok_wait(3 + wg);
        }
        mbar_wait(r.full(full0), r.phase());
        wg_fence();
        wgmma_ss_n160_tb1(acc, desc(da), desc(db, 0, bhi));
        wg_commit();
        if (ks <= 24 - NSLOT) {
          wg_wait<1>();
          if (!parked && elected) mbar_arrive_both(Ring{r.u - 1}.empty(full0), rank ^ 1);
        }
#pragma unroll
        for (int k = 1; k < 4; k++) wgmma_ss_n160_tb1(acc, desc(da, k * 32), desc(db, k * 2048, bhi));
        wg_commit();
        if (TAIL_L > 0 && ks == 23 && wg < 2) tok_pass(4 + wg);
        {
          if (ks == FL2_B1)      { landed(3, Int<0>{}); stage_in(pend);      send(1, 1); }
          else if (ks == FL2_B2) { landed(4, Int<0>{}); stage_in(pend + 16); send(1, 2); }
          else if (ks == FL2_LD) { landed(5, Int<0>{}); }
        }
        r.u++;
      }
      wg_wait<0>();
    }
    {
      const int lane = lane_id(), t = warp * 32 + lane;
#pragma unroll
      for (int q = 0; q < 4; q++) {
        const int blk0 = q == 0 ? 0 : q == 1 ? 6 : q == 2 ? 10 : 16, npk = (q & 1) ? 2 : 3;
        if (q != split) {
          const int dcta = (grp * 8 + 2 * q + (j8 & 1)) * 2 + rank;
          const int srcslot = split < q ? split : split - 1;
          uint4* dst = prm.part + (size_t)(dcta * 3 + srcslot) * (3 * 384) + t;
#pragma unroll
          for (int i = 0; i < 3; i++) {
            if (i < npk) {
              const int a = 4 * blk0 + 8 * i;
              __stcg(dst + i * 384, make_uint4(pack_bf16(acc[a], acc[a + 1]), pack_bf16(acc[a + 2], acc[a + 3]),
                                               pack_bf16(acc[a + 4], acc[a + 5]), pack_bf16(acc[a + 6], acc[a + 7])));
            }
          }
        }
      }
      __syncwarp();
      if (lane < 4 && lane != split) {
        const int dcta = (grp * 8 + 2 * lane + (j8 & 1)) * 2 + rank;
        red_release_add(&prm.xflag[dcta * 12 + warp], 1u);
      }
      const int nown = (split & 1) ? 2 : 3;
      float own[24];
#pragma unroll
      for (int i = 0; i < 24; i++)
        own[i] = split == 0 ? acc[i] : split == 1 ? acc[24 + (i & 15)] : split == 2 ? acc[40 + i] : acc[64 + (i & 15)];
      spin_until(&prm.xflag[cta * 12 + warp], target);
      {
        const uint4* src = prm.part + (size_t)(cta * 3) * (3 * 384) + t;
        uint4 v[9];
#pragma unroll
        for (int sidx = 0; sidx < 3; sidx++) {
          v[3 * sidx]     = __ldcg(src + (3 * sidx) * 384);
          v[3 * sidx + 1] = __ldcg(src + (3 * sidx + 1) * 384);
          v[3 * sidx + 2] = nown == 3 ? __ldcg(src + (3 * sidx + 2) * 384) : make_uint4(0u, 0u, 0u, 0u);
        }
#pragma unroll
        for (int sidx = 0; sidx < 3; sidx++) {
#pragma unroll
          for (int i = 0; i < 3; i++) {
            const uint32_t w[4] = {v[3 * sidx + i].x, v[3 * sidx + i].y, v[3 * sidx + i].z, v[3 * sidx + i].w};
#pragma unroll
            for (int k = 0; k < 4; k++) {
              own[8 * i + 2 * k]     += __uint_as_float(w[k] << 16);
              own[8 * i + 2 * k + 1] += __uint_as_float(w[k] & 0xffff0000u);
            }
          }
        }
      }
      stg_acquire();
      {
        const int r8 = lane & 7;
        const uint32_t st_base = wstg + (((lane >> 3) & 1) * 8 + r8) * 128;
#pragma unroll
        for (int jj = 0; jj < 3; jj++) {
          const uint32_t addr = st_base + (((2 * jj + (lane >> 4)) ^ r8) << 4);
          asm volatile("stmatrix.sync.aligned.m8n8.x4.shared.b16 [%0], {%1, %2, %3, %4};"
                       :: "r"(addr), "r"(pack_bf16(own[8 * jj], own[8 * jj + 1])), "r"(pack_bf16(own[8 * jj + 2], own[8 * jj + 3])),
                          "r"(pack_bf16(own[8 * jj + 4], own[8 * jj + 5])), "r"(pack_bf16(own[8 * jj + 6], own[8 * jj + 7])) : "memory");
        }
        __syncwarp();
        const int a0 = split == 0 ? 0 : split == 1 ? 48 : split == 2 ? 80 : 128;
        const int nch = 2 * nown;
        uint8_t* ob = reinterpret_cast<uint8_t*>(out) + ((size_t)(192 * bp + 16 * warp) * 1280 + 640 * prob + 320 * (j8 & 1)) * 2;
#pragma unroll
        for (int i = 0; i < 3; i++) {
          const int idx = i * 32 + lane;
          const int row = nown == 3 ? idx / 6 : idx >> 2, ch = idx - row * nch;
          if (row < 16) {
            uint4 w;
            asm volatile("ld.shared.v4.u32 {%0, %1, %2, %3}, [%4];" : "=r"(w.x), "=r"(w.y), "=r"(w.z), "=r"(w.w)
                         : "r"(wstg + row * 128 + ((ch ^ (row & 7)) << 4)) : "memory");
            const int a = a0 + 8 * ch;
            const int col = rank == 0 ? a : (a < 128 ? 192 + (a ^ 32) : 32 + a);
            *reinterpret_cast<uint4*>(ob + (size_t)row * 2560 + col * 2) = w;
          }
        }
      }
      if (t == 0) prm.epoch[cta] = otarget;
    }
  }
}

typedef CUresult (*EncodeFn)(CUtensorMap*, CUtensorMapDataType, cuuint32_t, void*, const cuuint64_t*, const cuuint64_t*,
                             const cuuint32_t*, const cuuint32_t*, CUtensorMapInterleave, CUtensorMapSwizzle,
                             CUtensorMapL2promotion, CUtensorMapFloatOOBfill);

void make_map(EncodeFn enc, CUtensorMap* m, const void* ptr, int rank, const uint64_t* dims, const uint64_t* strides,
              const uint32_t* box) {
  cuuint64_t d[3], s[2]; cuuint32_t b[3], e[3] = {1, 1, 1};
  for (int i = 0; i < rank; i++) { d[i] = dims[i]; b[i] = box[i]; }
  for (int i = 0; i + 1 < rank; i++) s[i] = strides[i];
  enc(m, CU_TENSOR_MAP_DATA_TYPE_BFLOAT16, rank, const_cast<void*>(ptr), d, s, b, e, CU_TENSOR_MAP_INTERLEAVE_NONE,
      CU_TENSOR_MAP_SWIZZLE_128B, CU_TENSOR_MAP_L2_PROMOTION_L2_128B, CU_TENSOR_MAP_FLOAT_OOB_FILL_NONE);
}

}

extern "C" void kernel_launch(void* const* d_in, const int* in_sizes, int n_in, void* d_out, int out_size) {
  (void)in_sizes; (void)n_in; (void)out_size;
  static EncodeFn enc = nullptr;
  static void *o_ptr = nullptr, *part_ptr = nullptr, *ready_ptr = nullptr, *xflag_ptr = nullptr, *epoch_ptr = nullptr;
  if (!enc) {
    void* fn = nullptr; cudaDriverEntryPointQueryResult st;
    cudaGetDriverEntryPoint("cuTensorMapEncodeTiled", &fn, cudaEnableDefault, &st);
    enc = (EncodeFn)fn;
    cudaGetSymbolAddress(&o_ptr, g_O);
    cudaGetSymbolAddress(&part_ptr, g_part);
    cudaGetSymbolAddress(&ready_ptr, g_ready);
    cudaGetSymbolAddress(&xflag_ptr, g_xflag);
    cudaGetSymbolAddress(&epoch_ptr, g_epoch);
    cudaFuncSetAttribute(fused_attn_kernel, cudaFuncAttributeMaxDynamicSharedMemorySize, SMEM_BYTES);
  }
  Params prm;
  for (int p = 0; p < 2; p++) {
    const void* x = d_in[5 * p + 0]; const void* k = d_in[5 * p + 1]; const void* v = d_in[5 * p + 2];
    const void* wq = d_in[5 * p + 3]; const void* wo = d_in[5 * p + 4];
    { uint64_t d[2] = {640, 768}, s[1] = {1280};              uint32_t b[2] = {64, 96};    make_map(enc, &prm.x[p],  x,  2, d, s, b); }
    { uint64_t d[2] = {640, 768}, s[1] = {1280};              uint32_t b[2] = {64, 192};   make_map(enc, &prm.x1[p], x,  2, d, s, b); }
    { uint64_t d[3] = {64, 640, 96}, s[2] = {12288, 128};     uint32_t b[3] = {64, 64, 3}; make_map(enc, &prm.wq[p], wq, 3, d, s, b); }
    { uint64_t d[3] = {64, 24576, 3}, s[2] = {384, 128};      uint32_t b[3] = {64, 96, 3}; make_map(enc, &prm.k[p],  k,  3, d, s, b); }
    { uint64_t d[3] = {64, 24576, 3}, s[2] = {384, 128};      uint32_t b[3] = {64, 96, 1}; make_map(enc, &prm.k1[p], k,  3, d, s, b); }
    { uint64_t d[3] = {64, 24576, 3}, s[2] = {384, 128};      uint32_t b[3] = {64, 96, 3}; make_map(enc, &prm.v[p],  v,  3, d, s, b); }
    { uint64_t d[3] = {64, 24576, 3}, s[2] = {384, 128};      uint32_t b[3] = {64, 96, 1}; make_map(enc, &prm.v1[p], v,  3, d, s, b); }
    prm.kptr[p] = (const uint8_t*)k; prm.vptr[p] = (const uint8_t*)v;
    prm.wqptr[p] = (const uint8_t*)wq;
    { uint64_t d[2] = {640, 6144}, s[1] = {1280};             uint32_t b[2] = {64, 64};    make_map(enc, &prm.wo[p], wo, 2, d, s, b); }
  }
  { uint64_t d[2] = {6144, 1536}, s[1] = {12288};        uint32_t b[2] = {64, 16};    make_map(enc, &prm.o_st, o_ptr, 2, d, s, b); }
  { uint64_t d[2] = {6144, 1536}, s[1] = {12288};        uint32_t b[2] = {64, 96};    make_map(enc, &prm.o_ld, o_ptr, 2, d, s, b); }
  prm.part = (uint4*)part_ptr; prm.ready = (unsigned*)ready_ptr; prm.xflag = (unsigned*)xflag_ptr; prm.epoch = (unsigned*)epoch_ptr;
  fused_attn_kernel<<<128, NTHREADS, SMEM_BYTES>>>(prm, (__nv_bfloat16*)d_out);
}
```

```cpp
#include <cuda_runtime.h>
#include <cuda_bf16.h>
#include <cuda.h>
#include <stdint.h>

namespace {

constexpr int FL_B1 = 2,  FL_B2 = 4,  FL_LD = 6;
constexpr int FL2_B1 = 3, FL2_B2 = 6, FL2_LD = 9;
constexpr int TAIL_L = 3;
constexpr int PF_WIN = 10;
constexpr int PF_R0 = 0, PF_R1 = 8, PF_R2 = 11, PF_R3 = 21;

constexpr int NTHREADS   = 512;
constexpr int NSLOT      = 4;
constexpr int SLOT_BYTES = 49152;
constexpr int B_OFF      = 24576;
constexpr int KV_BYTES   = 36864;
constexpr int STG_BYTES  = 12 * 2048;
constexpr int SMEM_BYTES = NSLOT * SLOT_BYTES + STG_BYTES + 1024  ;

struct Params {
  CUtensorMap x[2], x1[2], wq[2], k[2], k1[2], v[2], v1[2], wo[2];
  CUtensorMap o_st, o_ld;
  const uint8_t* kptr[2];
  const uint8_t* vptr[2];
  const uint8_t* wqptr[2];
  uint4*    part;
  unsigned* ready;
  unsigned* xflag;
  unsigned* epoch;
};

__host__ __device__ __forceinline__ int logical_cluster(int c) {
  const unsigned tab = 0xE6CA8421u;
  int v, bp;
  if (c < 4)       { v = 0; bp = c; }
  else if (c < 36) { const int t = c - 4;  v = (tab >> (4 * (t & 7))) & 15;          bp = t >> 3; }
  else             { const int t = c - 36; v = ((tab >> (4 * (1 + t % 7))) & 15) + 1; bp = t / 7; }
  return (v >> 3) * 32 + bp * 8 + (v & 7);
}

__device__ __nv_bfloat16 g_O[1536 * 6144];
__device__ uint4         g_part[128 * 3 * 3 * 384];
__device__ unsigned      g_ready[8 * 32];
__device__ unsigned      g_xflag[128 * 12];
__device__ unsigned      g_epoch[128];

__device__ __forceinline__ uint32_t smem_u32(const void* p) { return (uint32_t)__cvta_generic_to_shared(p); }
__device__ __forceinline__ void mbar_init(uint32_t bar, uint32_t count) {
  asm volatile("mbarrier.init.shared::cta.b64 [%0], %1;" :: "r"(bar), "r"(count) : "memory");
}
__device__ __forceinline__ void mbar_expect_tx(uint32_t bar, uint32_t bytes) {
  asm volatile("mbarrier.arrive.expect_tx.shared::cta.b64 _, [%0], %1;" :: "r"(bar), "r"(bytes) : "memory");
}
__device__ __forceinline__ void mbar_arrive_both(uint32_t bar, uint32_t peer) {
  asm volatile("{\n.reg .b32 r1;\n"
               "mapa.shared::cluster.u32 r1, %1, %2;\n"
               "mbarrier.arrive.shared::cta.b64 _, [%0];\n"
               "mbarrier.arrive.shared::cluster.b64 _, [r1];\n}"
               :: "r"(bar), "r"(bar + 8 * NSLOT), "r"(peer) : "memory");
}
__device__ __forceinline__ void mbar_wait(uint32_t bar, uint32_t parity) {
  asm volatile("{\n.reg .pred P1;\n.reg .u32 cnt;\nmov.u32 cnt, 0;\n"
               "LAB_WAIT:\n"
               "mbarrier.try_wait.parity.shared::cta.b64 P1, [%0], %1;\n"
               "@P1 bra DONE;\n"
               "add.u32 cnt, cnt, 1;\n"
               "setp.lt.u32 P1, cnt, 16777216;\n"
               "@P1 bra LAB_WAIT;\n"
               "trap;\n"
               "DONE:\n}"
               :: "r"(bar), "r"(parity) : "memory");
}
__device__ __forceinline__ uint64_t policy_evict_first() {
  uint64_t p; asm volatile("createpolicy.fractional.L2::evict_first.b64 %0, 1.0;" : "=l"(p)); return p;
}
__device__ __forceinline__ void tma_2d_nohint(uint32_t dst, const CUtensorMap* m, uint32_t bar, int c0, int c1) {
  asm volatile("cp.async.bulk.tensor.2d.shared::cluster.global.mbarrier::complete_tx::bytes [%0], [%1, {%3, %4}], [%2];"
               :: "r"(dst), "l"(m), "r"(bar), "r"(c0), "r"(c1) : "memory");
}
__device__ __forceinline__ void tma_2d_mc(uint32_t dst, const CUtensorMap* m, uint32_t bar, int c0, int c1) {
  asm volatile("cp.async.bulk.tensor.2d.shared::cluster.global.mbarrier::complete_tx::bytes.multicast::cluster [%0], [%1, {%3, %4}], [%2], %5;"
               :: "r"(dst), "l"(m), "r"(bar), "r"(c0), "r"(c1), "h"((uint16_t)3) : "memory");
}
__device__ __forceinline__ void tma_2d(uint32_t dst, const CUtensorMap* m, uint32_t bar, int c0, int c1, uint64_t pol) {
  asm volatile("cp.async.bulk.tensor.2d.shared::cluster.global.mbarrier::complete_tx::bytes.L2::cache_hint [%0], [%1, {%3, %4}], [%2], %5;"
               :: "r"(dst), "l"(m), "r"(bar), "r"(c0), "r"(c1), "l"(pol) : "memory");
}
__device__ __forceinline__ void tma_3d(uint32_t dst, const CUtensorMap* m, uint32_t bar, int c0, int c1, int c2, uint64_t pol) {
  asm volatile("cp.async.bulk.tensor.3d.shared::cluster.global.mbarrier::complete_tx::bytes.L2::cache_hint [%0], [%1, {%3, %4, %5}], [%2], %6;"
               :: "r"(dst), "l"(m), "r"(bar), "r"(c0), "r"(c1), "r"(c2), "l"(pol) : "memory");
}
__device__ __forceinline__ void tma_store_2d(const CUtensorMap* m, uint32_t src, int c0, int c1) {
  asm volatile("cp.async.bulk.tensor.2d.global.shared::cta.bulk_group [%0, {%2, %3}], [%1];"
               :: "l"(m), "r"(src), "r"(c0), "r"(c1) : "memory");
}
__device__ __forceinline__ bool mbar_test(uint32_t bar, uint32_t parity) {
  uint32_t ok;
  asm volatile("{\n.reg .pred p;\nmbarrier.test_wait.parity.shared::cta.b64 p, [%1], %2;\nselp.u32 %0, 1, 0, p;\n}"
               : "=r"(ok) : "r"(bar), "r"(parity) : "memory");
  return ok;
}
__device__ __forceinline__ int lane_id() { int l; asm volatile("mov.u32 %0, %%laneid;" : "=r"(l)); return l; }
__device__ __forceinline__ void mbar_arrive(uint32_t bar) {
  asm volatile("mbarrier.arrive.shared::cta.b64 _, [%0];" :: "r"(bar) : "memory");
}
__device__ __forceinline__ void wg_fence()  { asm volatile("wgmma.fence.sync.aligned;" ::: "memory"); }
__device__ __forceinline__ void wg_commit() { asm volatile("wgmma.commit_group.sync.aligned;" ::: "memory"); }
template <int N> __device__ __forceinline__ void wg_wait() { asm volatile("wgmma.wait_group.sync.aligned %0;" :: "n"(N) : "memory"); }
__device__ __forceinline__ void tok_wait(int id) { asm volatile("bar.sync %0, 256;" :: "r"(id) : "memory"); }
__device__ __forceinline__ void tok_pass(int id) { asm volatile("bar.arrive %0, 256;" :: "r"(id) : "memory"); }
__device__ __forceinline__ void cluster_arrive_relaxed() { asm volatile("barrier.cluster.arrive.relaxed.aligned;" ::: "memory"); }
__device__ __forceinline__ void cluster_wait()           { asm volatile("barrier.cluster.wait.aligned;" ::: "memory"); }
__device__ __forceinline__ unsigned ld_relaxed(const unsigned* p) {
  unsigned v; asm volatile("ld.relaxed.gpu.global.u32 %0, [%1];" : "=r"(v) : "l"(p) : "memory"); return v;
}
__device__ __forceinline__ unsigned ld_acquire(const unsigned* p) {
  unsigned v; asm volatile("ld.acquire.gpu.global.u32 %0, [%1];" : "=r"(v) : "l"(p) : "memory"); return v;
}
__device__ __forceinline__ void red_release_add(unsigned* p, unsigned v) {
  asm volatile("red.release.gpu.global.add.u32 [%0], %1;" :: "l"(p), "r"(v) : "memory");
}
__device__ __forceinline__ void spin_until(const unsigned* p, unsigned target) {
  asm volatile("{\n.reg .pred P1;\n.reg .u32 cnt, v;\nmov.u32 cnt, 0;\n"
               "LAB_SPIN:\n"
               "ld.acquire.gpu.global.u32 v, [%0];\n"
               "sub.u32 v, v, %1;\n"
               "setp.ge.s32 P1, v, 0;\n"
               "@P1 bra DONE;\n"
               "nanosleep.u32 20;\n"
               "add.u32 cnt, cnt, 1;\n"
               "setp.lt.u32 P1, cnt, 4194304;\n"
               "@P1 bra LAB_SPIN;\n"
               "trap;\n"
               "DONE:\n}"
               :: "l"(p), "r"(target) : "memory");
}
__device__ __forceinline__ uint32_t desc_lo(uint32_t addr, uint32_t lbo) { return ((addr & 0x3FFFF) >> 4) | ((lbo >> 4) << 16); }
__device__ __forceinline__ uint64_t desc(uint32_t lo, uint32_t byte_off = 0, uint32_t hi = 0x40000040u) {
  uint64_t d;
  asm("mov.b64 %0, {%1, %2};" : "=l"(d) : "r"(lo + (byte_off >> 4)), "r"(hi));
  return d;
}
__device__ __forceinline__ uint32_t pack_bf16(float lo, float hi) {
  uint32_t r; asm("cvt.rn.bf16x2.f32 %0, %1, %2;" : "=r"(r) : "f"(hi), "f"(lo)); return r;
}
__device__ __forceinline__ float ex2(float x) { float r; asm("ex2.approx.ftz.f32 %0, %1;" : "=f"(r) : "f"(x)); return r; }

__device__ __forceinline__ void wgmma_ss_n192_tb1(float (&d)[96], uint64_t descA, uint64_t descB) {
  asm volatile("{\n.reg .pred p;\n"
    "setp.ne.b32 p, 1, 0;\n"
    "wgmma.mma_async.sync.aligned.m64n192k16.f32.bf16.bf16 "
    "{%0, %1, %2, %3, %4, %5, %6, %7, %8, %9, %10, %11, %12, %13, %14, %15, "
    "%16, %17, %18, %19, %20, %21, %22, %23, %24, %25, %26, %27, %28, %29, %30, %31, "
    "%32, %33, %34, %35, %36, %37, %38, %39, %40, %41, %42, %43, %44, %45, %46, %47, "
    "%48, %49, %50, %51, %52, %53, %54, %55, %56, %57, %58, %59, %60, %61, %62, %63, "
    "%64, %65, %66, %67, %68, %69, %70, %71, %72, %73, %74, %75, %76, %77, %78, %79, "
    "%80, %81, %82, %83, %84, %85, %86, %87, %88, %89, %90, %91, %92, %93, %94, %95}, "
    "%96, %97, p, 1, 1, 0, 1;\n}\n"
    : "+f"(d[0]), "+f"(d[1]), "+f"(d[2]), "+f"(d[3]), "+f"(d[4]), "+f"(d[5]), "+f"(d[6]), "+f"(d[7]),
      "+f"(d[8]), "+f"(d[9]), "+f"(d[10]), "+f"(d[11]), "+f"(d[12]), "+f"(d[13]), "+f"(d[14]), "+f"(d[15]),
      "+f"(d[16]), "+f"(d[17]), "+f"(d[18]), "+f"(d[19]), "+f"(d[20]), "+f"(d[21]), "+f"(d[22]), "+f"(d[23]),
      "+f"(d[24]), "+f"(d[25]), "+f"(d[26]), "+f"(d[27]), "+f"(d[28]), "+f"(d[29]), "+f"(d[30]), "+f"(d[31]),
      "+f"(d[32]), "+f"(d[33]), "+f"(d[34]), "+f"(d[35]), "+f"(d[36]), "+f"(d[37]), "+f"(d[38]), "+f"(d[39]),
      "+f"(d[40]), "+f"(d[41]), "+f"(d[42]), "+f"(d[43]), "+f"(d[44]), "+f"(d[45]), "+f"(d[46]), "+f"(d[47]),
      "+f"(d[48]), "+f"(d[49]), "+f"(d[50]), "+f"(d[51]), "+f"(d[52]), "+f"(d[53]), "+f"(d[54]), "+f"(d[55]),
      "+f"(d[56]), "+f"(d[57]), "+f"(d[58]), "+f"(d[59]), "+f"(d[60]), "+f"(d[61]), "+f"(d[62]), "+f"(d[63]),
      "+f"(d[64]), "+f"(d[65]), "+f"(d[66]), "+f"(d[67]), "+f"(d[68]), "+f"(d[69]), "+f"(d[70]), "+f"(d[71]),
      "+f"(d[72]), "+f"(d[73]), "+f"(d[74]), "+f"(d[75]), "+f"(d[76]), "+f"(d[77]), "+f"(d[78]), "+f"(d[79]),
      "+f"(d[80]), "+f"(d[81]), "+f"(d[82]), "+f"(d[83]), "+f"(d[84]), "+f"(d[85]), "+f"(d[86]), "+f"(d[87]),
      "+f"(d[88]), "+f"(d[89]), "+f"(d[90]), "+f"(d[91]), "+f"(d[92]), "+f"(d[93]), "+f"(d[94]), "+f"(d[95])
    : "l"(descA), "l"(descB));
}

__device__ __forceinline__ void wgmma_ss_n192_tb1_init(float (&d)[96], uint64_t descA, uint64_t descB) {
  asm volatile("{\n.reg .pred p;\n"
    "setp.ne.b32 p, 0, 0;\n"
    "wgmma.mma_async.sync.aligned.m64n192k16.f32.bf16.bf16 "
    "{%0, %1, %2, %3, %4, %5, %6, %7, %8, %9, %10, %11, %12, %13, %14, %15, "
    "%16, %17, %18, %19, %20, %21, %22, %23, %24, %25, %26, %27, %28, %29, %30, %31, "
    "%32, %33, %34, %35, %36, %37, %38, %39, %40, %41, %42, %43, %44, %45, %46, %47, "
    "%48, %49, %50, %51, %52, %53, %54, %55, %56, %57, %58, %59, %60, %61, %62, %63, "
    "%64, %65, %66, %67, %68, %69, %70, %71, %72, %73, %74, %75, %76, %77, %78, %79, "
    "%80, %81, %82, %83, %84, %85, %86, %87, %88, %89, %90, %91, %92, %93, %94, %95}, "
    "%96, %97, p, 1, 1, 0, 1;\n}\n"
    : "=f"(d[0]), "=f"(d[1]), "=f"(d[2]), "=f"(d[3]), "=f"(d[4]), "=f"(d[5]), "=f"(d[6]), "=f"(d[7]),
      "=f"(d[8]), "=f"(d[9]), "=f"(d[10]), "=f"(d[11]), "=f"(d[12]), "=f"(d[13]), "=f"(d[14]), "=f"(d[15]),
      "=f"(d[16]), "=f"(d[17]), "=f"(d[18]), "=f"(d[19]), "=f"(d[20]), "=f"(d[21]), "=f"(d[22]), "=f"(d[23]),
      "=f"(d[24]), "=f"(d[25]), "=f"(d[26]), "=f"(d[27]), "=f"(d[28]), "=f"(d[29]), "=f"(d[30]), "=f"(d[31]),
      "=f"(d[32]), "=f"(d[33]), "=f"(d[34]), "=f"(d[35]), "=f"(d[36]), "=f"(d[37]), "=f"(d[38]), "=f"(d[39]),
      "=f"(d[40]), "=f"(d[41]), "=f"(d[42]), "=f"(d[43]), "=f"(d[44]), "=f"(d[45]), "=f"(d[46]), "=f"(d[47]),
      "=f"(d[48]), "=f"(d[49]), "=f"(d[50]), "=f"(d[51]), "=f"(d[52]), "=f"(d[53]), "=f"(d[54]), "=f"(d[55]),
      "=f"(d[56]), "=f"(d[57]), "=f"(d[58]), "=f"(d[59]), "=f"(d[60]), "=f"(d[61]), "=f"(d[62]), "=f"(d[63]),
      "=f"(d[64]), "=f"(d[65]), "=f"(d[66]), "=f"(d[67]), "=f"(d[68]), "=f"(d[69]), "=f"(d[70]), "=f"(d[71]),
      "=f"(d[72]), "=f"(d[73]), "=f"(d[74]), "=f"(d[75]), "=f"(d[76]), "=f"(d[77]), "=f"(d[78]), "=f"(d[79]),
      "=f"(d[80]), "=f"(d[81]), "=f"(d[82]), "=f"(d[83]), "=f"(d[84]), "=f"(d[85]), "=f"(d[86]), "=f"(d[87]),
      "=f"(d[88]), "=f"(d[89]), "=f"(d[90]), "=f"(d[91]), "=f"(d[92]), "=f"(d[93]), "=f"(d[94]), "=f"(d[95])
    : "l"(descA), "l"(descB));
}

__device__ __forceinline__ void wgmma_ss_n160_tb1(float (&d)[80], uint64_t descA, uint64_t descB) {
  asm volatile("{\n.reg .pred p;\n"
    "setp.ne.b32 p, 1, 0;\n"
    "wgmma.mma_async.sync.aligned.m64n160k16.f32.bf16.bf16 "
    "{%0, %1, %2, %3, %4, %5, %6, %7, %8, %9, %10, %11, %12, %13, %14, %15, "
    "%16, %17, %18, %19, %20, %21, %22, %23, %24, %25, %26, %27, %28, %29, %30, %31, "
    "%32, %33, %34, %35, %36, %37, %38, %39, %40, %41, %42, %43, %44, %45, %46, %47, "
    "%48, %49, %50, %51, %52, %53, %54, %55, %56, %57, %58, %59, %60, %61, %62, %63, "
    "%64, %65, %66, %67, %68, %69, %70, %71, %72, %73, %74, %75, %76, %77, %78, %79}, "
    "%80, %81, p, 1, 1, 0, 1;\n}\n"
    : "+f"(d[0]), "+f"(d[1]), "+f"(d[2]), "+f"(d[3]), "+f"(d[4]), "+f"(d[5]), "+f"(d[6]), "+f"(d[7]),
      "+f"(d[8]), "+f"(d[9]), "+f"(d[10]), "+f"(d[11]), "+f"(d[12]), "+f"(d[13]), "+f"(d[14]), "+f"(d[15]),
      "+f"(d[16]), "+f"(d[17]), "+f"(d[18]), "+f"(d[19]), "+f"(d[20]), "+f"(d[21]), "+f"(d[22]), "+f"(d[23]),
      "+f"(d[24]), "+f"(d[25]), "+f"(d[26]), "+f"(d[27]), "+f"(d[28]), "+f"(d[29]), "+f"(d[30]), "+f"(d[31]),
      "+f"(d[32]), "+f"(d[33]), "+f"(d[34]), "+f"(d[35]), "+f"(d[36]), "+f"(d[37]), "+f"(d[38]), "+f"(d[39]),
      "+f"(d[40]), "+f"(d[41]), "+f"(d[42]), "+f"(d[43]), "+f"(d[44]), "+f"(d[45]), "+f"(d[46]), "+f"(d[47]),
      "+f"(d[48]), "+f"(d[49]), "+f"(d[50]), "+f"(d[51]), "+f"(d[52]), "+f"(d[53]), "+f"(d[54]), "+f"(d[55]),
      "+f"(d[56]), "+f"(d[57]), "+f"(d[58]), "+f"(d[59]), "+f"(d[60]), "+f"(d[61]), "+f"(d[62]), "+f"(d[63]),
      "+f"(d[64]), "+f"(d[65]), "+f"(d[66]), "+f"(d[67]), "+f"(d[68]), "+f"(d[69]), "+f"(d[70]), "+f"(d[71]),
      "+f"(d[72]), "+f"(d[73]), "+f"(d[74]), "+f"(d[75]), "+f"(d[76]), "+f"(d[77]), "+f"(d[78]), "+f"(d[79])
    : "l"(descA), "l"(descB));
}

__device__ __forceinline__ void wgmma_ss_n160_tb1_init(float (&d)[80], uint64_t descA, uint64_t descB) {
  asm volatile("{\n.reg .pred p;\n"
    "setp.ne.b32 p, 0, 0;\n"
    "wgmma.mma_async.sync.aligned.m64n160k16.f32.bf16.bf16 "
    "{%0, %1, %2, %3, %4, %5, %6, %7, %8, %9, %10, %11, %12, %13, %14, %15, "
    "%16, %17, %18, %19, %20, %21, %22, %23, %24, %25, %26, %27, %28, %29, %30, %31, "
    "%32, %33, %34, %35, %36, %37, %38, %39, %40, %41, %42, %43, %44, %45, %46, %47, "
    "%48, %49, %50, %51, %52, %53, %54, %55, %56, %57, %58, %59, %60, %61, %62, %63, "
    "%64, %65, %66, %67, %68, %69, %70, %71, %72, %73, %74, %75, %76, %77, %78, %79}, "
    "%80, %81, p, 1, 1, 0, 1;\n}\n"
    : "=f"(d[0]), "=f"(d[1]), "=f"(d[2]), "=f"(d[3]), "=f"(d[4]), "=f"(d[5]), "=f"(d[6]), "=f"(d[7]),
      "=f"(d[8]), "=f"(d[9]), "=f"(d[10]), "=f"(d[11]), "=f"(d[12]), "=f"(d[13]), "=f"(d[14]), "=f"(d[15]),
      "=f"(d[16]), "=f"(d[17]), "=f"(d[18]), "=f"(d[19]), "=f"(d[20]), "=f"(d[21]), "=f"(d[22]), "=f"(d[23]),
      "=f"(d[24]), "=f"(d[25]), "=f"(d[26]), "=f"(d[27]), "=f"(d[28]), "=f"(d[29]), "=f"(d[30]), "=f"(d[31]),
      "=f"(d[32]), "=f"(d[33]), "=f"(d[34]), "=f"(d[35]), "=f"(d[36]), "=f"(d[37]), "=f"(d[38]), "=f"(d[39]),
      "=f"(d[40]), "=f"(d[41]), "=f"(d[42]), "=f"(d[43]), "=f"(d[44]), "=f"(d[45]), "=f"(d[46]), "=f"(d[47]),
      "=f"(d[48]), "=f"(d[49]), "=f"(d[50]), "=f"(d[51]), "=f"(d[52]), "=f"(d[53]), "=f"(d[54]), "=f"(d[55]),
      "=f"(d[56]), "=f"(d[57]), "=f"(d[58]), "=f"(d[59]), "=f"(d[60]), "=f"(d[61]), "=f"(d[62]), "=f"(d[63]),
      "=f"(d[64]), "=f"(d[65]), "=f"(d[66]), "=f"(d[67]), "=f"(d[68]), "=f"(d[69]), "=f"(d[70]), "=f"(d[71]),
      "=f"(d[72]), "=f"(d[73]), "=f"(d[74]), "=f"(d[75]), "=f"(d[76]), "=f"(d[77]), "=f"(d[78]), "=f"(d[79])
    : "l"(descA), "l"(descB));
}

__device__ __forceinline__ void wgmma_rs_n96_tb0(float (&d)[48], uint32_t a0, uint32_t a1, uint32_t a2, uint32_t a3, uint64_t descB) {
  asm volatile("{\n.reg .pred p;\n"
    "setp.ne.b32 p, 1, 0;\n"
    "wgmma.mma_async.sync.aligned.m64n96k16.f32.bf16.bf16 "
    "{%0, %1, %2, %3, %4, %5, %6, %7, %8, %9, %10, %11, %12, %13, %14, %15, "
    "%16, %17, %18, %19, %20, %21, %22, %23, %24, %25, %26, %27, %28, %29, %30, %31, "
    "%32, %33, %34, %35, %36, %37, %38, %39, %40, %41, %42, %43, %44, %45, %46, %47}, "
    "{%48, %49, %50, %51}, %52, p, 1, 1, 0;\n}\n"
    : "+f"(d[0]), "+f"(d[1]), "+f"(d[2]), "+f"(d[3]), "+f"(d[4]), "+f"(d[5]), "+f"(d[6]), "+f"(d[7]),
      "+f"(d[8]), "+f"(d[9]), "+f"(d[10]), "+f"(d[11]), "+f"(d[12]), "+f"(d[13]), "+f"(d[14]), "+f"(d[15]),
      "+f"(d[16]), "+f"(d[17]), "+f"(d[18]), "+f"(d[19]), "+f"(d[20]), "+f"(d[21]), "+f"(d[22]), "+f"(d[23]),
      "+f"(d[24]), "+f"(d[25]), "+f"(d[26]), "+f"(d[27]), "+f"(d[28]), "+f"(d[29]), "+f"(d[30]), "+f"(d[31]),
      "+f"(d[32]), "+f"(d[33]), "+f"(d[34]), "+f"(d[35]), "+f"(d[36]), "+f"(d[37]), "+f"(d[38]), "+f"(d[39]),
      "+f"(d[40]), "+f"(d[41]), "+f"(d[42]), "+f"(d[43]), "+f"(d[44]), "+f"(d[45]), "+f"(d[46]), "+f"(d[47])
    : "r"(a0), "r"(a1), "r"(a2), "r"(a3), "l"(descB));
}

__device__ __forceinline__ void wgmma_rs_n96_tb0_init(float (&d)[48], uint32_t a0, uint32_t a1, uint32_t a2, uint32_t a3, uint64_t descB) {
  asm volatile("{\n.reg .pred p;\n"
    "setp.ne.b32 p, 0, 0;\n"
    "wgmma.mma_async.sync.aligned.m64n96k16.f32.bf16.bf16 "
    "{%0, %1, %2, %3, %4, %5, %6, %7, %8, %9, %10, %11, %12, %13, %14, %15, "
    "%16, %17, %18, %19, %20, %21, %22, %23, %24, %25, %26, %27, %28, %29, %30, %31, "
    "%32, %33, %34, %35, %36, %37, %38, %39, %40, %41, %42, %43, %44, %45, %46, %47}, "
    "{%48, %49, %50, %51}, %52, p, 1, 1, 0;\n}\n"
    : "=f"(d[0]), "=f"(d[1]), "=f"(d[2]), "=f"(d[3]), "=f"(d[4]), "=f"(d[5]), "=f"(d[6]), "=f"(d[7]),
      "=f"(d[8]), "=f"(d[9]), "=f"(d[10]), "=f"(d[11]), "=f"(d[12]), "=f"(d[13]), "=f"(d[14]), "=f"(d[15]),
      "=f"(d[16]), "=f"(d[17]), "=f"(d[18]), "=f"(d[19]), "=f"(d[20]), "=f"(d[21]), "=f"(d[22]), "=f"(d[23]),
      "=f"(d[24]), "=f"(d[25]), "=f"(d[26]), "=f"(d[27]), "=f"(d[28]), "=f"(d[29]), "=f"(d[30]), "=f"(d[31]),
      "=f"(d[32]), "=f"(d[33]), "=f"(d[34]), "=f"(d[35]), "=f"(d[36]), "=f"(d[37]), "=f"(d[38]), "=f"(d[39]),
      "=f"(d[40]), "=f"(d[41]), "=f"(d[42]), "=f"(d[43]), "=f"(d[44]), "=f"(d[45]), "=f"(d[46]), "=f"(d[47])
    : "r"(a0), "r"(a1), "r"(a2), "r"(a3), "l"(descB));
}

__device__ __forceinline__ void wgmma_rs_n128_tb1(float (&d)[64], uint32_t a0, uint32_t a1, uint32_t a2, uint32_t a3, uint64_t descB) {
  asm volatile("{\n.reg .pred p;\n"
    "setp.ne.b32 p, 1, 0;\n"
    "wgmma.mma_async.sync.aligned.m64n128k16.f32.bf16.bf16 "
    "{%0, %1, %2, %3, %4, %5, %6, %7, %8, %9, %10, %11, %12, %13, %14, %15, "
    "%16, %17, %18, %19, %20, %21, %22, %23, %24, %25, %26, %27, %28, %29, %30, %31, "
    "%32, %33, %34, %35, %36, %37, %38, %39, %40, %41, %42, %43, %44, %45, %46, %47, "
    "%48, %49, %50, %51, %52, %53, %54, %55, %56, %57, %58, %59, %60, %61, %62, %63}, "
    "{%64, %65, %66, %67}, %68, p, 1, 1, 1;\n}\n"
    : "+f"(d[0]), "+f"(d[1]), "+f"(d[2]), "+f"(d[3]), "+f"(d[4]), "+f"(d[5]), "+f"(d[6]), "+f"(d[7]),
      "+f"(d[8]), "+f"(d[9]), "+f"(d[10]), "+f"(d[11]), "+f"(d[12]), "+f"(d[13]), "+f"(d[14]), "+f"(d[15]),
      "+f"(d[16]), "+f"(d[17]), "+f"(d[18]), "+f"(d[19]), "+f"(d[20]), "+f"(d[21]), "+f"(d[22]), "+f"(d[23]),
      "+f"(d[24]), "+f"(d[25]), "+f"(d[26]), "+f"(d[27]), "+f"(d[28]), "+f"(d[29]), "+f"(d[30]), "+f"(d[31]),
      "+f"(d[32]), "+f"(d[33]), "+f"(d[34]), "+f"(d[35]), "+f"(d[36]), "+f"(d[37]), "+f"(d[38]), "+f"(d[39]),
      "+f"(d[40]), "+f"(d[41]), "+f"(d[42]), "+f"(d[43]), "+f"(d[44]), "+f"(d[45]), "+f"(d[46]), "+f"(d[47]),
      "+f"(d[48]), "+f"(d[49]), "+f"(d[50]), "+f"(d[51]), "+f"(d[52]), "+f"(d[53]), "+f"(d[54]), "+f"(d[55]),
      "+f"(d[56]), "+f"(d[57]), "+f"(d[58]), "+f"(d[59]), "+f"(d[60]), "+f"(d[61]), "+f"(d[62]), "+f"(d[63])
    : "r"(a0), "r"(a1), "r"(a2), "r"(a3), "l"(descB));
}

__device__ __forceinline__ void wgmma_rs_n128_tb1_init(float (&d)[64], uint32_t a0, uint32_t a1, uint32_t a2, uint32_t a3, uint64_t descB) {
  asm volatile("{\n.reg .pred p;\n"
    "setp.ne.b32 p, 0, 0;\n"
    "wgmma.mma_async.sync.aligned.m64n128k16.f32.bf16.bf16 "
    "{%0, %1, %2, %3, %4, %5, %6, %7, %8, %9, %10, %11, %12, %13, %14, %15, "
    "%16, %17, %18, %19, %20, %21, %22, %23, %24, %25, %26, %27, %28, %29, %30, %31, "
    "%32, %33, %34, %35, %36, %37, %38, %39, %40, %41, %42, %43, %44, %45, %46, %47, "
    "%48, %49, %50, %51, %52, %53, %54, %55, %56, %57, %58, %59, %60, %61, %62, %63}, "
    "{%64, %65, %66, %67}, %68, p, 1, 1, 1;\n}\n"
    : "=f"(d[0]), "=f"(d[1]), "=f"(d[2]), "=f"(d[3]), "=f"(d[4]), "=f"(d[5]), "=f"(d[6]), "=f"(d[7]),
      "=f"(d[8]), "=f"(d[9]), "=f"(d[10]), "=f"(d[11]), "=f"(d[12]), "=f"(d[13]), "=f"(d[14]), "=f"(d[15]),
      "=f"(d[16]), "=f"(d[17]), "=f"(d[18]), "=f"(d[19]), "=f"(d[20]), "=f"(d[21]), "=f"(d[22]), "=f"(d[23]),
      "=f"(d[24]), "=f"(d[25]), "=f"(d[26]), "=f"(d[27]), "=f"(d[28]), "=f"(d[29]), "=f"(d[30]), "=f"(d[31]),
      "=f"(d[32]), "=f"(d[33]), "=f"(d[34]), "=f"(d[35]), "=f"(d[36]), "=f"(d[37]), "=f"(d[38]), "=f"(d[39]),
      "=f"(d[40]), "=f"(d[41]), "=f"(d[42]), "=f"(d[43]), "=f"(d[44]), "=f"(d[45]), "=f"(d[46]), "=f"(d[47]),
      "=f"(d[48]), "=f"(d[49]), "=f"(d[50]), "=f"(d[51]), "=f"(d[52]), "=f"(d[53]), "=f"(d[54]), "=f"(d[55]),
      "=f"(d[56]), "=f"(d[57]), "=f"(d[58]), "=f"(d[59]), "=f"(d[60]), "=f"(d[61]), "=f"(d[62]), "=f"(d[63])
    : "r"(a0), "r"(a1), "r"(a2), "r"(a3), "l"(descB));
}

__device__ __forceinline__ void wgmma_rs_n64_tb1(float (&d)[32], uint32_t a0, uint32_t a1, uint32_t a2, uint32_t a3, uint64_t descB) {
  asm volatile("{\n.reg .pred p;\n"
    "setp.ne.b32 p, 1, 0;\n"
    "wgmma.mma_async.sync.aligned.m64n64k16.f32.bf16.bf16 "
    "{%0, %1, %2, %3, %4, %5, %6, %7, %8, %9, %10, %11, %12, %13, %14, %15, "
    "%16, %17, %18, %19, %20, %21, %22, %23, %24, %25, %26, %27, %28, %29, %30, %31}, "
    "{%32, %33, %34, %35}, %36, p, 1, 1, 1;\n}\n"
    : "+f"(d[0]), "+f"(d[1]), "+f"(d[2]), "+f"(d[3]), "+f"(d[4]), "+f"(d[5]), "+f"(d[6]), "+f"(d[7]),
      "+f"(d[8]), "+f"(d[9]), "+f"(d[10]), "+f"(d[11]), "+f"(d[12]), "+f"(d[13]), "+f"(d[14]), "+f"(d[15]),
      "+f"(d[16]), "+f"(d[17]), "+f"(d[18]), "+f"(d[19]), "+f"(d[20]), "+f"(d[21]), "+f"(d[22]), "+f"(d[23]),
      "+f"(d[24]), "+f"(d[25]), "+f"(d[26]), "+f"(d[27]), "+f"(d[28]), "+f"(d[29]), "+f"(d[30]), "+f"(d[31])
    : "r"(a0), "r"(a1), "r"(a2), "r"(a3), "l"(descB));
}

__device__ __forceinline__ void wgmma_rs_n64_tb1_init(float (&d)[32], uint32_t a0, uint32_t a1, uint32_t a2, uint32_t a3, uint64_t descB) {
  asm volatile("{\n.reg .pred p;\n"
    "setp.ne.b32 p, 0, 0;\n"
    "wgmma.mma_async.sync.aligned.m64n64k16.f32.bf16.bf16 "
    "{%0, %1, %2, %3, %4, %5, %6, %7, %8, %9, %10, %11, %12, %13, %14, %15, "
    "%16, %17, %18, %19, %20, %21, %22, %23, %24, %25, %26, %27, %28, %29, %30, %31}, "
    "{%32, %33, %34, %35}, %36, p, 1, 1, 1;\n}\n"
    : "=f"(d[0]), "=f"(d[1]), "=f"(d[2]), "=f"(d[3]), "=f"(d[4]), "=f"(d[5]), "=f"(d[6]), "=f"(d[7]),
      "=f"(d[8]), "=f"(d[9]), "=f"(d[10]), "=f"(d[11]), "=f"(d[12]), "=f"(d[13]), "=f"(d[14]), "=f"(d[15]),
      "=f"(d[16]), "=f"(d[17]), "=f"(d[18]), "=f"(d[19]), "=f"(d[20]), "=f"(d[21]), "=f"(d[22]), "=f"(d[23]),
      "=f"(d[24]), "=f"(d[25]), "=f"(d[26]), "=f"(d[27]), "=f"(d[28]), "=f"(d[29]), "=f"(d[30]), "=f"(d[31])
    : "r"(a0), "r"(a1), "r"(a2), "r"(a3), "l"(descB));
}

template <int V> struct Int { static constexpr int value = V; };

struct Ring {
  uint32_t u;
  __device__ __forceinline__ uint32_t slot()  const { return u & (NSLOT - 1); }
  __device__ __forceinline__ uint32_t phase() const { return (u >> 2) & 1; }
  __device__ __forceinline__ uint32_t full(uint32_t full0)   const { return full0 + 8 * slot(); }
  __device__ __forceinline__ uint32_t empty(uint32_t full0)  const { return full0 + 8 * NSLOT + 8 * slot(); }
  __device__ __forceinline__ uint32_t addr(uint32_t ring)    const { return ring + slot() * SLOT_BYTES; }
  __device__ __forceinline__ Ring operator+(uint32_t d) const { return Ring{u + d}; }
};

__device__ __forceinline__ void softmax96(float (&s)[48], uint32_t (&p)[24], float& r0, float& r1) {
  const float c = 0.07216878364870322f * 1.4426950408889634f;
  float a0[6], a1[6];
#pragma unroll
  for (int j = 0; j < 6; j++) {
    a0[j] = fmaxf(fmaxf(s[8 * j], s[8 * j + 1]), fmaxf(s[8 * j + 4], s[8 * j + 5]));
    a1[j] = fmaxf(fmaxf(s[8 * j + 2], s[8 * j + 3]), fmaxf(s[8 * j + 6], s[8 * j + 7]));
  }
  float m0 = fmaxf(fmaxf(fmaxf(a0[0], a0[1]), fmaxf(a0[2], a0[3])), fmaxf(a0[4], a0[5]));
  float m1 = fmaxf(fmaxf(fmaxf(a1[0], a1[1]), fmaxf(a1[2], a1[3])), fmaxf(a1[4], a1[5]));
  m0 = fmaxf(m0, __shfl_xor_sync(0xffffffffu, m0, 1));
  m1 = fmaxf(m1, __shfl_xor_sync(0xffffffffu, m1, 1));
  m0 = fmaxf(m0, __shfl_xor_sync(0xffffffffu, m0, 2));
  m1 = fmaxf(m1, __shfl_xor_sync(0xffffffffu, m1, 2));
  const float b0 = -m0 * c, b1 = -m1 * c;
  float l0 = 0.f, l1 = 0.f;
#pragma unroll
  for (int j = 0; j < 12; j++) {
    const float e0 = ex2(fmaf(s[4 * j],     c, b0)), e1 = ex2(fmaf(s[4 * j + 1], c, b0));
    const float e2 = ex2(fmaf(s[4 * j + 2], c, b1)), e3 = ex2(fmaf(s[4 * j + 3], c, b1));
    l0 += e0 + e1;
    l1 += e2 + e3;
    p[2 * j]     = pack_bf16(e0, e1);
    p[2 * j + 1] = pack_bf16(e2, e3);
  }
  l0 += __shfl_xor_sync(0xffffffffu, l0, 1);
  l1 += __shfl_xor_sync(0xffffffffu, l1, 1);
  l0 += __shfl_xor_sync(0xffffffffu, l0, 2);
  l1 += __shfl_xor_sync(0xffffffffu, l1, 2);
  asm("rcp.approx.ftz.f32 %0, %1;" : "=f"(r0) : "f"(l0));
  asm("rcp.approx.ftz.f32 %0, %1;" : "=f"(r1) : "f"(l1));
}

template <bool INIT>
__device__ __forceinline__ void qk_mma(float (&s)[48], const uint32_t (&qf)[48], uint32_t box0, uint32_t box1, uint32_t box2, int pass_id) {
  const uint32_t d0 = desc_lo(box0, 16), d1 = desc_lo(box1, 16), d2 = desc_lo(box2, 16);
  if (INIT) wgmma_rs_n96_tb0_init(s, qf[0], qf[1], qf[2], qf[3], desc(d0));
  else      wgmma_rs_n96_tb0(s, qf[0], qf[1], qf[2], qf[3], desc(d0));
#pragma unroll
  for (int k = 1; k < 12; k++) {
    wgmma_rs_n96_tb0(s, qf[4 * k], qf[4 * k + 1], qf[4 * k + 2], qf[4 * k + 3], desc(k < 4 ? d0 : k < 8 ? d1 : d2, (k & 3) * 32));
  }
  tok_pass(pass_id);
}
template <bool INIT>
__device__ __forceinline__ void pv_mma(float (&o)[96], const uint32_t (&pf)[24], uint32_t box01, uint32_t box2, int pass_id) {
  float (&oa)[64] = *reinterpret_cast<float (*)[64]>(&o[0]);
  float (&ob)[32] = *reinterpret_cast<float (*)[32]>(&o[64]);
  const uint32_t da = desc_lo(box01, 12288), db = desc_lo(box2, 12288);
  if (INIT) { wgmma_rs_n128_tb1_init(oa, pf[0], pf[1], pf[2], pf[3], desc(da)); wgmma_rs_n64_tb1_init(ob, pf[0], pf[1], pf[2], pf[3], desc(db)); }
  else      { wgmma_rs_n128_tb1(oa, pf[0], pf[1], pf[2], pf[3], desc(da));      wgmma_rs_n64_tb1(ob, pf[0], pf[1], pf[2], pf[3], desc(db)); }
#pragma unroll
  for (int k = 1; k < 6; k++) {
    wgmma_rs_n128_tb1(oa, pf[4 * k], pf[4 * k + 1], pf[4 * k + 2], pf[4 * k + 3], desc(da, k * 2048));
    wgmma_rs_n64_tb1(ob, pf[4 * k], pf[4 * k + 1], pf[4 * k + 2], pf[4 * k + 3], desc(db, k * 2048));
  }
  tok_pass(pass_id);
}

__global__ void __cluster_dims__(2, 1, 1) __launch_bounds__(NTHREADS, 1)
fused_attn_kernel(const __grid_constant__ Params prm, __nv_bfloat16* __restrict__ out) {
  extern __shared__ uint8_t smem_raw[];
  __shared__ uint64_t s_bars[3 * NSLOT + 10];
  __shared__ uint32_t s_dummy[64];
  __shared__ volatile uint32_t s_prog;

  const uint32_t ring = (smem_u32(smem_raw) + 1023) & ~1023u;
  const uint32_t stg  = ring + NSLOT * SLOT_BYTES;
  const uint32_t full0 = smem_u32(&s_bars[0]);
  const uint32_t o_done  = full0 + 24 * NSLOT;
  const uint32_t o_ready = o_done + 48;

  const int tid = threadIdx.x, lane = tid & 31;
  const int warp = __shfl_sync(0xffffffffu, tid >> 5, 0);
  const int rank = blockIdx.x & 1, cl = logical_cluster(blockIdx.x >> 1), cta = 2 * cl + rank;
  const int grp = cl >> 3, prob = grp >> 2, bp = grp & 3, j8 = cl & 7;
  const int split = j8 >> 1;

  if (tid == 13 * 32) {
    asm volatile("prefetch.tensormap [%0];" :: "l"(&prm.wq[prob]) : "memory");
    asm volatile("prefetch.tensormap [%0];" :: "l"(&prm.x1[prob]) : "memory");
    asm volatile("prefetch.tensormap [%0];" :: "l"(&prm.x[prob]) : "memory");
  }
  if (tid == 12 * 32) {
#pragma unroll
    for (int s = 0; s < NSLOT; s++) { mbar_init(full0 + 8 * s, 1); mbar_init(full0 + 8 * NSLOT + 8 * s, 3); mbar_init(full0 + 16 * NSLOT + 8 * s, 3); }
    for (int s = 0; s < 6; s++) mbar_init(o_done + 8 * s, 12);
    for (int s = 0; s < 4; s++) mbar_init(o_ready + 8 * s, 1);
    s_prog = NSLOT;
    asm volatile("fence.mbarrier_init.release.cluster;" ::: "memory");
  }
  __syncthreads();
  cluster_arrive_relaxed();
  if (tid == 12 * 32) {
    const int h = 2 * j8 + rank;
    const uint64_t pol = policy_evict_first();
#pragma unroll
    for (int s = 0; s < NSLOT; s++) {
      mbar_expect_tx(full0 + 8 * s, SLOT_BYTES);
      tma_2d_nohint(ring + s * SLOT_BYTES, &prm.x1[prob], full0 + 8 * s, 64 * s, 192 * bp);
      tma_3d(ring + s * SLOT_BYTES + B_OFF, &prm.wq[prob], full0 + 8 * s, 0, 64 * s, 3 * h, pol);
    }
  }
  __syncwarp();
  cluster_wait();

  if (warp >= 12) {
    asm volatile("setmaxnreg.dec.sync.aligned.u32 32;");
    if (warp == 12) {
      if (lane == 0) {
        Ring r{0};
        const uint64_t pol_s = policy_evict_first();
        const int ncol0 = 320 * (j8 & 1);
#pragma unroll 1
        for (int w = 0; w < 2; w++) {
          const int h = 16 * w + 2 * j8 + rank;
#pragma unroll 1
          for (int ks = 0; ks < 10; ks++) {
            const uint32_t fb = r.full(full0), sl = r.addr(ring);
            if (r.u >= NSLOT) {
              mbar_wait(r.empty(full0), r.phase() ^ 1);
              mbar_expect_tx(fb, SLOT_BYTES);
              s_prog = r.u;
              tma_3d(sl + B_OFF, &prm.wq[prob], fb, 0, 64 * ks, 3 * h, pol_s);
              mbar_wait(r.empty(full0) + 8 * NSLOT, r.phase() ^ 1);
              tma_2d_mc(sl + rank * 12288, &prm.x[prob], fb, 64 * ks, 192 * bp + 96 * rank);
            }
            r.u++;
          }
#pragma unroll 1
          for (int t = 0; t < 3; t++) {
            const uint32_t fb = r.full(full0), sl = r.addr(ring);
            const int row0 = ((2 * bp) * 32 + h) * 96, row1 = row0 + 32 * 96;
            mbar_wait(r.empty(full0), r.phase() ^ 1);
            mbar_expect_tx(fb, SLOT_BYTES);
            s_prog = r.u;
            if (t == 0) {
              tma_3d(sl,         &prm.k[prob],  fb, 0, row0, 0, pol_s);
              tma_3d(sl + 36864, &prm.k1[prob], fb, 0, row1, 0, pol_s);
            } else if (t == 1) {
              tma_3d(sl,         &prm.k1[prob], fb, 0, row1, 1, pol_s);
              tma_3d(sl + 12288, &prm.k1[prob], fb, 0, row1, 2, pol_s);
              tma_3d(sl + 24576, &prm.v1[prob], fb, 0, row0, 0, pol_s);
              tma_3d(sl + 36864, &prm.v1[prob], fb, 0, row0, 1, pol_s);
            } else {
              tma_3d(sl,         &prm.v1[prob], fb, 0, row0, 2, pol_s);
              tma_3d(sl + 12288, &prm.v[prob],  fb, 0, row1, 0, pol_s);
            }
            mbar_wait(r.empty(full0) + 8 * NSLOT, r.phase() ^ 1);
            r.u++;
          }
        }
#pragma unroll 1
        for (int i = 0; i < 24; i++) {
          const int h = i < 12 ? 4 * split + i / 3 : 16 + 4 * split + (i & 3);
          const int c = i < 12 ? i % 3 : (i - 12) >> 2;
          const uint32_t fb = r.full(full0), sl = r.addr(ring);
          const int k0 = h * 192 + c * 64;
          mbar_wait(r.empty(full0), r.phase() ^ 1);
          mbar_expect_tx(fb, SLOT_BYTES);
          s_prog = r.u;
          tma_2d(sl + B_OFF,         &prm.wo[prob],   fb, ncol0 + 192 * rank,      k0, pol_s);
          tma_2d(sl + B_OFF + 8192,  &prm.wo[prob],   fb, ncol0 + 192 * rank + 64, k0, pol_s);
          tma_2d(sl + B_OFF + 16384, &prm.wo[prob],   fb, ncol0 + 128, k0, pol_s);
          if (i == 0 || (i >= 12 && (i & 3) == 0)) {
            mbar_wait(o_ready + 8 * (i == 0 ? 0 : (i >> 2) - 2), 0);
          }
          mbar_wait(r.empty(full0) + 8 * NSLOT, r.phase() ^ 1);
          tma_2d_mc(sl + rank * 12288, &prm.o_ld, fb, k0, prob * 768 + 192 * bp + 96 * rank);
          r.u++;
        }
      }
    } else if (warp == 13) {
      {
        const unsigned obase = 3u * ld_relaxed(&prm.epoch[cta]);
        uint32_t pub = 0, wat = 0;
#pragma unroll 1
        for (int it = 0; it < (1 << 22) && (pub < 6 || wat < 4); it++) {
          if (pub < 6 && mbar_test(o_done + 8 * pub, 0)) {
            uint32_t n = 1;
            while ((pub + n) % 3 != 0 && mbar_test(o_done + 8 * (pub + n), 0)) n++;
            if (lane == 0) {
              red_release_add(&prm.ready[grp * 32 + 16 * (pub >= 3) + 2 * j8 + rank], n);
            }
            __syncwarp();
            pub += n;
          } else if (wat < 4 && pub > wat + 2) {
            const unsigned tgt = obase + (wat == 0 ? 3u : wat);
            const unsigned a = ld_acquire(&prm.ready[grp * 32 + (wat == 0 ? 0 : 16) + 4 * split + (lane & 3)]);
            if (__all_sync(0xffffffffu, (int)(a - tgt) >= 0)) {
              if (lane == 0) {
                asm volatile("fence.proxy.async;" ::: "memory");
                mbar_arrive(o_ready + 8 * wat);
              }
              __syncwarp();
              wat++;
            }
          } else {
            mbar_wait(o_done + 8 * pub, 0);
          }
        }
      }
    } else {
      const int h0 = 2 * j8 + rank;
      const uint8_t* wqp = prm.wqptr[prob];
      auto addr_of = [&](int n) -> const uint8_t* {
        if (n < 9 || (n >= 45 && n < 60)) {
          const bool second = n >= 45;
          const int i = (second ? n - 45 : n + 6) * 32 + lane;
          const int ks = i / 48, rem = i - ks * 48;
          return wqp + (size_t)(64 * ks + 16 * bp + rem / 3) * 12288 + (h0 + (second ? 16 : 0)) * 384 + (rem % 3) * 128;
        }
        const bool second = n >= 60;
        const int m = second ? n - 60 : n - 9, tile = m / 9;
        const uint8_t* base = (tile < 2) ? prm.kptr[prob] : prm.vptr[prob];
        return base + (size_t)((2 * bp + (tile & 1)) * 32 + h0 + (second ? 16 : 0)) * KV_BYTES + (m - 9 * tile) * 4096 + lane * 128;
      };
      auto use_of = [&](int n) -> int {
        if (n < 9)  return ((n + 6) * 32) / 48;
        if (n < 45) { const int t = (n - 9) / 9; return 10 + (t < 2 ? 0 : t - 1); }
        if (n < 60) return 13 + ((n - 45) * 32) / 48;
        const int t = (n - 60) / 9;
        return 23 + (t < 2 ? 0 : t - 1);
      };
      auto release_of = [&](int n) -> int {
        if (n < 9)  return 0;
        if (n < 45) return PF_R0 + ((n - 9) * (PF_R1 - PF_R0)) / 36;
        if (n < 60) return PF_R1 + ((n - 45) * (PF_R2 - PF_R1)) / 15;
        return PF_R2 + ((n - 60) * (PF_R3 - PF_R2)) / 36;
      };
      const uint32_t dummy = smem_u32(&s_dummy[tid & 63]);
#pragma unroll 1
      for (int n = warp - 14; n < 96; n += 2) {
        const int u = use_of(n), rel = release_of(n);
        int guard = 0;
        while ((int)s_prog < rel && ++guard < (1 << 20)) __nanosleep(100);
        if ((int)s_prog < u)
          asm volatile("cp.async.ca.shared.global.L2::128B [%0], [%1], 4;" :: "r"(dummy), "l"(addr_of(n)) : "memory");
        asm volatile("cp.async.commit_group;" ::: "memory");
        asm volatile("cp.async.wait_group %0;" :: "n"(PF_WIN) : "memory");
      }
      asm volatile("cp.async.wait_group 0;" ::: "memory");
    }
  } else {
    asm volatile("setmaxnreg.inc.sync.aligned.u32 160;");
    const int wg = warp >> 2, wq4 = warp & 3;
    const bool elected = wq4 == 0 && lane_id() == 0;
    const uint32_t descA0 = desc_lo(ring + wg * 8192, 16), descB0 = desc_lo(ring + B_OFF, 8192);
    Ring r{0};
    uint32_t pend[32];
    const uint32_t wstg = stg + warp * 2048;
    auto stg_acquire = [&]() {
      if (lane_id() == 0) asm volatile("cp.async.bulk.wait_group.read 0;" ::: "memory");
      __syncwarp();
    };
    auto stage_in = [&](const uint32_t* v) {
      stg_acquire();
      const int lane = lane_id(), r8 = lane & 7;
      const uint32_t st_base = wstg + (((lane >> 3) & 1) * 8 + r8) * 128;
#pragma unroll
      for (int jj = 0; jj < 4; jj++) {
        const uint32_t addr = st_base + (((2 * jj + (lane >> 4)) ^ r8) << 4);
        asm volatile("stmatrix.sync.aligned.m8n8.x4.shared.b16 [%0], {%1, %2, %3, %4};"
                     :: "r"(addr), "r"(v[4 * jj]), "r"(v[4 * jj + 1]), "r"(v[4 * jj + 2]), "r"(v[4 * jj + 3]) : "memory");
      }
    };
    auto send = [&](int wv, int box) {
      asm volatile("fence.proxy.async.shared::cta;" ::: "memory");
      __syncwarp();
      if (lane_id() == 0) {
        tma_store_2d(&prm.o_st, wstg, (16 * wv + 2 * j8 + rank) * 192 + 64 * box, prob * 768 + 192 * bp + 16 * warp);
        asm volatile("cp.async.bulk.commit_group;" ::: "memory");
      }
    };
    auto landed = [&](int ev, auto pending) {
      if (lane_id() == 0) {
        asm volatile("cp.async.bulk.wait_group %0;" :: "n"(decltype(pending)::value) : "memory");
        mbar_arrive(o_done + 8 * ev);
      }
    };

#pragma unroll 1
    for (int w = 0; w < 2; w++) {
      uint32_t qf[48];
      {
        float acc[96];
        {
          const uint32_t da = descA0 + r.slot() * (SLOT_BYTES >> 4), db = descB0 + r.slot() * (SLOT_BYTES >> 4);
          mbar_wait(r.full(full0), r.phase());
          if (w > 0) { if (wg == 0) tok_wait(14); else if (wg == 2) tok_wait(15); }
          wg_fence();
          wgmma_ss_n192_tb1_init(acc, desc(da), desc(db));
#pragma unroll
          for (int k = 1; k < 4; k++) wgmma_ss_n192_tb1(acc, desc(da, k * 32), desc(db, k * 2048));
          wg_commit();
          if (w > 0 && wg == 0) tok_pass(15);
          if (w > 0) send(0, 0);
          r.u++;
        }
#pragma unroll 1
        for (int ks = 1; ks < 8; ks++) {
          const uint32_t da = descA0 + r.slot() * (SLOT_BYTES >> 4), db = descB0 + r.slot() * (SLOT_BYTES >> 4);
          mbar_wait(r.full(full0), r.phase());
          wg_fence();
          wgmma_ss_n192_tb1(acc, desc(da), desc(db));
          wg_commit();
          wg_wait<1>();
          if (elected) mbar_arrive_both(Ring{r.u - 1}.empty(full0), rank ^ 1);
#pragma unroll
          for (int k = 1; k < 4; k++) wgmma_ss_n192_tb1(acc, desc(da, k * 32), desc(db, k * 2048));
          wg_commit();
          if (w > 0) {
            if (ks == FL_B1)      { stage_in(pend);      send(0, 1); }
            else if (ks == FL_B2) { stage_in(pend + 16); send(0, 2); }
            else if (ks == FL_LD) { landed(0, Int<0>{}); landed(1, Int<0>{}); landed(2, Int<0>{}); }
          }
          r.u++;
        }
        {
          const Ring r8 = r, r9 = r + 1;
          r.u += 2;
          wg_wait<0>();
          if (elected) mbar_arrive_both(Ring{r8.u - 1}.empty(full0), rank ^ 1);
          mbar_wait(r8.full(full0), r8.phase());
          mbar_wait(r9.full(full0), r9.phase());
          if (wg != 1) tok_wait(wg == 0 ? 4 : 5);
          const uint32_t da8 = descA0 + r8.slot() * (SLOT_BYTES >> 4), db8 = descB0 + r8.slot() * (SLOT_BYTES >> 4);
          const uint32_t da9 = descA0 + r9.slot() * (SLOT_BYTES >> 4), db9 = descB0 + r9.slot() * (SLOT_BYTES >> 4);
          wg_fence();
#pragma unroll
          for (int k = 0; k < 4; k++) wgmma_ss_n192_tb1(acc, desc(da8, k * 32), desc(db8, k * 2048));
          wg_commit();
#pragma unroll
          for (int k = 0; k < 4; k++) wgmma_ss_n192_tb1(acc, desc(da9, k * 32), desc(db9, k * 2048));
          wg_commit();
          if (wg != 2) tok_pass(wg == 1 ? 4 : 5);
          wg_wait<1>();
          if (elected) mbar_arrive_both(r8.empty(full0), rank ^ 1);
          mbar_wait(r.full(full0), r.phase());
          if (wg == 2) mbar_wait((r + 1).full(full0), (r + 1).phase());
          wg_wait<0>();
          if (elected) mbar_arrive_both(r9.empty(full0), rank ^ 1);
        }
        stg_acquire();
        const int lane = lane_id();
#pragma unroll
        for (int i = 0; i < 4; i++)
          asm volatile("st.shared.v4.u32 [%0], {%1, %2, %3, %4};"
                       :: "r"(wstg + i * 512 + lane * 16),
                          "r"(pack_bf16(acc[64 + 8 * i], acc[65 + 8 * i])), "r"(pack_bf16(acc[66 + 8 * i], acc[67 + 8 * i])),
                          "r"(pack_bf16(acc[68 + 8 * i], acc[69 + 8 * i])), "r"(pack_bf16(acc[70 + 8 * i], acc[71 + 8 * i])) : "memory");
#pragma unroll
        for (int i = 0; i < 32; i++) qf[i] = pack_bf16(acc[2 * i], acc[2 * i + 1]);
        asm volatile("" ::: "memory");
#pragma unroll
        for (int i = 0; i < 4; i++)
          asm volatile("ld.shared.v4.u32 {%0, %1, %2, %3}, [%4];"
                       : "=r"(qf[32 + 4 * i]), "=r"(qf[33 + 4 * i]), "=r"(qf[34 + 4 * i]), "=r"(qf[35 + 4 * i])
                       : "r"(wstg + i * 512 + lane * 16) : "memory");
      }
      const Ring rX = r, rY = r + 1, rZ = r + 2;
      r.u += 3;
      uint32_t pf[24];
      float rinv0, rinv1;
      bool z_ready;
      const uint32_t aX = rX.addr(ring), aY = rY.addr(ring), aZ = rZ.addr(ring);
      {
        float s[48];
        if (wg != 1) tok_wait(wg == 0 ? 7 : 9);
        wg_fence();
        qk_mma<true>(s, qf, wg == 2 ? aX + 36864 : aX, wg == 2 ? aY : aX + 12288, wg == 2 ? aY + 12288 : aX + 24576, wg == 1 ? 7 : wg == 0 ? 8 : 10);
        wg_commit();
        if (wg != 2) mbar_wait(rY.full(full0), rY.phase());
        wg_wait<0>();
        if (wg == 1) {
          if (wq4 < 2) {
#pragma unroll
            for (int i = 0; i < 48; i++) qf[i] = 0u;
          } else {
#pragma unroll
            for (int i = 0; i < 48; i++) s[i] = 0.f;
          }
          tok_wait(8);
          wg_fence();
          qk_mma<false>(s, qf, aX + 36864, aY, aY + 12288, 9);
          wg_commit();
          wg_wait<0>();
        }
        if (elected) { mbar_arrive_both(rX.empty(full0), rank ^ 1); if (wg == 2) mbar_arrive_both(rY.empty(full0), rank ^ 1); }
        __syncwarp();
        z_ready = mbar_test(rZ.full(full0), rZ.phase());
        softmax96(s, pf, rinv0, rinv1);
      }
      float o[96];
      {
        if (!__all_sync(0xffffffffu, z_ready)) mbar_wait(rZ.full(full0), rZ.phase());
        tok_wait(wg == 0 ? 10 : wg == 1 ? 11 : 12);
        wg_fence();
        pv_mma<true>(o, pf, wg == 2 ? aZ + 12288 : aY + 24576, wg == 2 ? aZ + 36864 : aZ, wg == 0 ? 11 : wg == 1 ? 12 : 13);
        wg_commit();
        wg_wait<0>();
        if (wg == 1) {
          if (elected) mbar_arrive_both(rY.empty(full0), rank ^ 1);
          if (wq4 < 2) {
#pragma unroll
            for (int i = 0; i < 24; i++) pf[i] = 0u;
          } else {
#pragma unroll
            for (int i = 0; i < 96; i++) o[i] = 0.f;
          }
          tok_wait(13);
          wg_fence();
          pv_mma<false>(o, pf, aZ + 12288, aZ + 36864, 14);
          wg_commit();
          wg_wait<0>();
        }
        if (elected) { if (wg == 0) mbar_arrive_both(rY.empty(full0), rank ^ 1); mbar_arrive_both(rZ.empty(full0), rank ^ 1); }
      }
      {
        uint32_t v[16];
#pragma unroll
        for (int i = 0; i < 16; i++) { const float ri = (i & 1) ? rinv1 : rinv0; v[i] = pack_bf16(o[2 * i] * ri, o[2 * i + 1] * ri); }
#pragma unroll
        for (int i = 0; i < 32; i++) { const float ri = (i & 1) ? rinv1 : rinv0; pend[i] = pack_bf16(o[32 + 2 * i] * ri, o[33 + 2 * i] * ri); }
        stage_in(v);
      }
    }

    const unsigned otarget = ld_relaxed(&prm.epoch[cta]) + 1u, target = 3u * otarget;
    const uint32_t bhi = 0x40000040u | (rank ? 4u << 17 : 0u);
    float acc[80];
    {
      {
        const uint32_t da = descA0 + r.slot() * (SLOT_BYTES >> 4), db = descB0 + r.slot() * (SLOT_BYTES >> 4);
        mbar_wait(r.full(full0), r.phase());
        if (wg == 0) tok_wait(14); else if (wg == 2) tok_wait(15);
        wg_fence();
        wgmma_ss_n160_tb1_init(acc, desc(da), desc(db, 0, bhi));
#pragma unroll
        for (int k = 1; k < 4; k++) wgmma_ss_n160_tb1(acc, desc(da, k * 32), desc(db, k * 2048, bhi));
        wg_commit();
        if (wg == 0) tok_pass(15);
        send(1, 0);
        r.u++;
      }
#pragma unroll 1
      for (int ks = 1; ks < 24 - TAIL_L; ks++) {
        const uint32_t da = descA0 + r.slot() * (SLOT_BYTES >> 4), db = descB0 + r.slot() * (SLOT_BYTES >> 4);
        mbar_wait(r.full(full0), r.phase());
        wg_fence();
        wgmma_ss_n160_tb1(acc, desc(da), desc(db, 0, bhi));
        wg_commit();
        wg_wait<1>();
        if (elected) mbar_arrive_both(Ring{r.u - 1}.empty(full0), rank ^ 1);
#pragma unroll
        for (int k = 1; k < 4; k++) wgmma_ss_n160_tb1(acc, desc(da, k * 32), desc(db, k * 2048, bhi));
        wg_commit();
        {
          if (ks == FL2_B1)      { landed(3, Int<0>{}); stage_in(pend);      send(1, 1); }
          else if (ks == FL2_B2) { landed(4, Int<0>{}); stage_in(pend + 16); send(1, 2); }
          else if (ks == FL2_LD) { landed(5, Int<0>{}); }
        }
        r.u++;
      }
      static_assert(TAIL_L == NSLOT - 1, "the slots of the last NSLOT ring uses are not released");
      if (wg > 0) {
#pragma unroll
        for (int i = 0; i < TAIL_L; i++) mbar_wait((r + i).full(full0), (r + i).phase());
        tok_wait(3 + wg);
      } else {
        mbar_wait(r.full(full0), r.phase());
        mbar_wait((r + 1).full(full0), (r + 1).phase());
      }
      wg_fence();
#pragma unroll
      for (int i = 0; i < TAIL_L; i++) {
        const uint32_t da = descA0 + (r + i).slot() * (SLOT_BYTES >> 4), db = descB0 + (r + i).slot() * (SLOT_BYTES >> 4);
        if (i == TAIL_L - 1 && wg == 0) mbar_wait((r + i).full(full0), (r + i).phase());
#pragma unroll
        for (int k = 0; k < 4; k++) wgmma_ss_n160_tb1(acc, desc(da, k * 32), desc(db, k * 2048, bhi));
      }
      wg_commit();
      if (wg < 2) tok_pass(4 + wg);
      wg_wait<0>();
    }
    {
      const int lane = lane_id(), t = warp * 32 + lane;
#pragma unroll
      for (int q = 0; q < 4; q++) {
        const int blk0 = q == 0 ? 0 : q == 1 ? 6 : q == 2 ? 10 : 16, npk = (q & 1) ? 2 : 3;
        if (q != split) {
          const int dcta = (grp * 8 + 2 * q + (j8 & 1)) * 2 + rank;
          const int srcslot = split < q ? split : split - 1;
          uint4* dst = prm.part + (size_t)(dcta * 3 + srcslot) * (3 * 384) + t;
#pragma unroll
          for (int i = 0; i < 3; i++) {
            if (i < npk) {
              const int a = 4 * blk0 + 8 * i;
              __stcg(dst + i * 384, make_uint4(pack_bf16(acc[a], acc[a + 1]), pack_bf16(acc[a + 2], acc[a + 3]),
                                               pack_bf16(acc[a + 4], acc[a + 5]), pack_bf16(acc[a + 6], acc[a + 7])));
            }
          }
        }
      }
      __syncwarp();
      if (lane < 4 && lane != split) {
        const int dcta = (grp * 8 + 2 * lane + (j8 & 1)) * 2 + rank;
        red_release_add(&prm.xflag[dcta * 12 + warp], 1u);
      }
      const int nown = (split & 1) ? 2 : 3;
      float own[24];
#pragma unroll
      for (int i = 0; i < 24; i++)
        own[i] = split == 0 ? acc[i] : split == 1 ? acc[24 + (i & 15)] : split == 2 ? acc[40 + i] : acc[64 + (i & 15)];
      spin_until(&prm.xflag[cta * 12 + warp], target);
      {
        const uint4* src = prm.part + (size_t)(cta * 3) * (3 * 384) + t;
        uint4 v[9];
#pragma unroll
        for (int sidx = 0; sidx < 3; sidx++) {
          v[3 * sidx]     = __ldcg(src + (3 * sidx) * 384);
          v[3 * sidx + 1] = __ldcg(src + (3 * sidx + 1) * 384);
          v[3 * sidx + 2] = nown == 3 ? __ldcg(src + (3 * sidx + 2) * 384) : make_uint4(0u, 0u, 0u, 0u);
        }
#pragma unroll
        for (int sidx = 0; sidx < 3; sidx++) {
#pragma unroll
          for (int i = 0; i < 3; i++) {
            const uint32_t w[4] = {v[3 * sidx + i].x, v[3 * sidx + i].y, v[3 * sidx + i].z, v[3 * sidx + i].w};
#pragma unroll
            for (int k = 0; k < 4; k++) {
              own[8 * i + 2 * k]     += __uint_as_float(w[k] << 16);
              own[8 * i + 2 * k + 1] += __uint_as_float(w[k] & 0xffff0000u);
            }
          }
        }
      }
      stg_acquire();
      {
        const int r8 = lane & 7;
        const uint32_t st_base = wstg + (((lane >> 3) & 1) * 8 + r8) * 128;
#pragma unroll
        for (int jj = 0; jj < 3; jj++) {
          const uint32_t addr = st_base + (((2 * jj + (lane >> 4)) ^ r8) << 4);
          asm volatile("stmatrix.sync.aligned.m8n8.x4.shared.b16 [%0], {%1, %2, %3, %4};"
                       :: "r"(addr), "r"(pack_bf16(own[8 * jj], own[8 * jj + 1])), "r"(pack_bf16(own[8 * jj + 2], own[8 * jj + 3])),
                          "r"(pack_bf16(own[8 * jj + 4], own[8 * jj + 5])), "r"(pack_bf16(own[8 * jj + 6], own[8 * jj + 7])) : "memory");
        }
        __syncwarp();
        const int a0 = split == 0 ? 0 : split == 1 ? 48 : split == 2 ? 80 : 128;
        const int nch = 2 * nown;
        uint8_t* ob = reinterpret_cast<uint8_t*>(out) + ((size_t)(192 * bp + 16 * warp) * 1280 + 640 * prob + 320 * (j8 & 1)) * 2;
#pragma unroll
        for (int i = 0; i < 3; i++) {
          const int idx = i * 32 + lane;
          const int row = nown == 3 ? idx / 6 : idx >> 2, ch = idx - row * nch;
          if (row < 16) {
            uint4 w;
            asm volatile("ld.shared.v4.u32 {%0, %1, %2, %3}, [%4];" : "=r"(w.x), "=r"(w.y), "=r"(w.z), "=r"(w.w)
                         : "r"(wstg + row * 128 + ((ch ^ (row & 7)) << 4)) : "memory");
            const int a = a0 + 8 * ch;
            const int col = rank == 0 ? a : (a < 128 ? 192 + (a ^ 32) : 32 + a);
            *reinterpret_cast<uint4*>(ob + (size_t)row * 2560 + col * 2) = w;
          }
        }
      }
      if (t == 0) prm.epoch[cta] = otarget;
    }
  }
}

typedef CUresult (*EncodeFn)(CUtensorMap*, CUtensorMapDataType, cuuint32_t, void*, const cuuint64_t*, const cuuint64_t*,
                             const cuuint32_t*, const cuuint32_t*, CUtensorMapInterleave, CUtensorMapSwizzle,
                             CUtensorMapL2promotion, CUtensorMapFloatOOBfill);

void make_map(EncodeFn enc, CUtensorMap* m, const void* ptr, int rank, const uint64_t* dims, const uint64_t* strides,
              const uint32_t* box) {
  cuuint64_t d[3], s[2]; cuuint32_t b[3], e[3] = {1, 1, 1};
  for (int i = 0; i < rank; i++) { d[i] = dims[i]; b[i] = box[i]; }
  for (int i = 0; i + 1 < rank; i++) s[i] = strides[i];
  enc(m, CU_TENSOR_MAP_DATA_TYPE_BFLOAT16, rank, const_cast<void*>(ptr), d, s, b, e, CU_TENSOR_MAP_INTERLEAVE_NONE,
      CU_TENSOR_MAP_SWIZZLE_128B, CU_TENSOR_MAP_L2_PROMOTION_L2_128B, CU_TENSOR_MAP_FLOAT_OOB_FILL_NONE);
}

}

extern "C" void kernel_launch(void* const* d_in, const int* in_sizes, int n_in, void* d_out, int out_size) {
  (void)in_sizes; (void)n_in; (void)out_size;
  static EncodeFn enc = nullptr;
  static void *o_ptr = nullptr, *part_ptr = nullptr, *ready_ptr = nullptr, *xflag_ptr = nullptr, *epoch_ptr = nullptr;
  if (!enc) {
    void* fn = nullptr; cudaDriverEntryPointQueryResult st;
    cudaGetDriverEntryPoint("cuTensorMapEncodeTiled", &fn, cudaEnableDefault, &st);
    enc = (EncodeFn)fn;
    cudaGetSymbolAddress(&o_ptr, g_O);
    cudaGetSymbolAddress(&part_ptr, g_part);
    cudaGetSymbolAddress(&ready_ptr, g_ready);
    cudaGetSymbolAddress(&xflag_ptr, g_xflag);
    cudaGetSymbolAddress(&epoch_ptr, g_epoch);
    cudaFuncSetAttribute(fused_attn_kernel, cudaFuncAttributeMaxDynamicSharedMemorySize, SMEM_BYTES);
  }
  Params prm;
  for (int p = 0; p < 2; p++) {
    const void* x = d_in[5 * p + 0]; const void* k = d_in[5 * p + 1]; const void* v = d_in[5 * p + 2];
    const void* wq = d_in[5 * p + 3]; const void* wo = d_in[5 * p + 4];
    { uint64_t d[2] = {640, 768}, s[1] = {1280};              uint32_t b[2] = {64, 96};    make_map(enc, &prm.x[p],  x,  2, d, s, b); }
    { uint64_t d[2] = {640, 768}, s[1] = {1280};              uint32_t b[2] = {64, 192};   make_map(enc, &prm.x1[p], x,  2, d, s, b); }
    { uint64_t d[3] = {64, 640, 96}, s[2] = {12288, 128};     uint32_t b[3] = {64, 64, 3}; make_map(enc, &prm.wq[p], wq, 3, d, s, b); }
    { uint64_t d[3] = {64, 24576, 3}, s[2] = {384, 128};      uint32_t b[3] = {64, 96, 3}; make_map(enc, &prm.k[p],  k,  3, d, s, b); }
    { uint64_t d[3] = {64, 24576, 3}, s[2] = {384, 128};      uint32_t b[3] = {64, 96, 1}; make_map(enc, &prm.k1[p], k,  3, d, s, b); }
    { uint64_t d[3] = {64, 24576, 3}, s[2] = {384, 128};      uint32_t b[3] = {64, 96, 3}; make_map(enc, &prm.v[p],  v,  3, d, s, b); }
    { uint64_t d[3] = {64, 24576, 3}, s[2] = {384, 128};      uint32_t b[3] = {64, 96, 1}; make_map(enc, &prm.v1[p], v,  3, d, s, b); }
    prm.kptr[p] = (const uint8_t*)k; prm.vptr[p] = (const uint8_t*)v;
    prm.wqptr[p] = (const uint8_t*)wq;
    { uint64_t d[2] = {640, 6144}, s[1] = {1280};             uint32_t b[2] = {64, 64};    make_map(enc, &prm.wo[p], wo, 2, d, s, b); }
  }
  { uint64_t d[2] = {6144, 1536}, s[1] = {12288};        uint32_t b[2] = {64, 16};    make_map(enc, &prm.o_st, o_ptr, 2, d, s, b); }
  { uint64_t d[2] = {6144, 1536}, s[1] = {12288};        uint32_t b[2] = {64, 96};    make_map(enc, &prm.o_ld, o_ptr, 2, d, s, b); }
  prm.part = (uint4*)part_ptr; prm.ready = (unsigned*)ready_ptr; prm.xflag = (unsigned*)xflag_ptr; prm.epoch = (unsigned*)epoch_ptr;
  fused_attn_kernel<<<128, NTHREADS, SMEM_BYTES>>>(prm, (__nv_bfloat16*)d_out);
}
```

```cpp
#include <cuda_runtime.h>
#include <cuda_bf16.h>
#include <cuda.h>
#include <stdint.h>

namespace {

constexpr int FL_B1 = 2,  FL_B2 = 5,  FL_LD = 7;
constexpr int FL2_B1 = 2, FL2_B2 = 5, FL2_LD = 8;
constexpr int TAIL_L = 3;
constexpr int PF_WIN = 10;
constexpr int PF_R0 = 0, PF_R1 = 8, PF_R2 = 11, PF_R3 = 21;

constexpr int NTHREADS   = 512;
constexpr int NSLOT      = 4;
constexpr int SLOT_BYTES = 49152;
constexpr int B_OFF      = 24576;
constexpr int KV_BYTES   = 36864;
constexpr int STG_BYTES  = 12 * 2048;
constexpr int SMEM_BYTES = NSLOT * SLOT_BYTES + STG_BYTES + 1024  ;

struct Params {
  CUtensorMap x[2], x1[2], wq[2], k[2], k1[2], v[2], v1[2], wo[2];
  CUtensorMap o_st, o_ld;
  const uint8_t* kptr[2];
  const uint8_t* vptr[2];
  const uint8_t* wqptr[2];
  uint4*    part;
  unsigned* ready;
  unsigned* xflag;
  unsigned* epoch;
};

__host__ __device__ __forceinline__ int logical_cluster(int c) {
  const unsigned tab = 0xE6CA8421u;
  int v, bp;
  if (c < 4)       { v = 0; bp = c; }
  else if (c < 36) { const int t = c - 4;  v = (tab >> (4 * (t & 7))) & 15;          bp = t >> 3; }
  else             { const int t = c - 36; v = ((tab >> (4 * (1 + t % 7))) & 15) + 1; bp = t / 7; }
  return (v >> 3) * 32 + bp * 8 + (v & 7);
}

__device__ __nv_bfloat16 g_O[1536 * 6144];
__device__ uint4         g_part[128 * 3 * 3 * 384];
__device__ unsigned      g_ready[8 * 32];
__device__ unsigned      g_xflag[128 * 12];
__device__ unsigned      g_epoch[128];

__device__ __forceinline__ uint32_t smem_u32(const void* p) { return (uint32_t)__cvta_generic_to_shared(p); }
__device__ __forceinline__ void mbar_init(uint32_t bar, uint32_t count) {
  asm volatile("mbarrier.init.shared::cta.b64 [%0], %1;" :: "r"(bar), "r"(count) : "memory");
}
__device__ __forceinline__ void mbar_expect_tx(uint32_t bar, uint32_t bytes) {
  asm volatile("mbarrier.arrive.expect_tx.shared::cta.b64 _, [%0], %1;" :: "r"(bar), "r"(bytes) : "memory");
}
__device__ __forceinline__ void mbar_arrive_both(uint32_t bar, uint32_t peer) {
  asm volatile("{\n.reg .b32 r1;\n"
               "mapa.shared::cluster.u32 r1, %1, %2;\n"
               "mbarrier.arrive.shared::cta.b64 _, [%0];\n"
               "mbarrier.arrive.shared::cluster.b64 _, [r1];\n}"
               :: "r"(bar), "r"(bar + 8 * NSLOT), "r"(peer) : "memory");
}
__device__ __forceinline__ void mbar_wait(uint32_t bar, uint32_t parity) {
  asm volatile("{\n.reg .pred P1;\n.reg .u32 cnt;\nmov.u32 cnt, 0;\n"
               "LAB_WAIT:\n"
               "mbarrier.try_wait.parity.shared::cta.b64 P1, [%0], %1;\n"
               "@P1 bra DONE;\n"
               "add.u32 cnt, cnt, 1;\n"
               "setp.lt.u32 P1, cnt, 16777216;\n"
               "@P1 bra LAB_WAIT;\n"
               "trap;\n"
               "DONE:\n}"
               :: "r"(bar), "r"(parity) : "memory");
}
__device__ __forceinline__ uint64_t policy_evict_first() {
  uint64_t p; asm volatile("createpolicy.fractional.L2::evict_first.b64 %0, 1.0;" : "=l"(p)); return p;
}
__device__ __forceinline__ void tma_2d_nohint(uint32_t dst, const CUtensorMap* m, uint32_t bar, int c0, int c1) {
  asm volatile("cp.async.bulk.tensor.2d.shared::cluster.global.mbarrier::complete_tx::bytes [%0], [%1, {%3, %4}], [%2];"
               :: "r"(dst), "l"(m), "r"(bar), "r"(c0), "r"(c1) : "memory");
}
__device__ __forceinline__ void tma_2d_mc(uint32_t dst, const CUtensorMap* m, uint32_t bar, int c0, int c1) {
  asm volatile("cp.async.bulk.tensor.2d.shared::cluster.global.mbarrier::complete_tx::bytes.multicast::cluster [%0], [%1, {%3, %4}], [%2], %5;"
               :: "r"(dst), "l"(m), "r"(bar), "r"(c0), "r"(c1), "h"((uint16_t)3) : "memory");
}
__device__ __forceinline__ void tma_2d(uint32_t dst, const CUtensorMap* m, uint32_t bar, int c0, int c1, uint64_t pol) {
  asm volatile("cp.async.bulk.tensor.2d.shared::cluster.global.mbarrier::complete_tx::bytes.L2::cache_hint [%0], [%1, {%3, %4}], [%2], %5;"
               :: "r"(dst), "l"(m), "r"(bar), "r"(c0), "r"(c1), "l"(pol) : "memory");
}
__device__ __forceinline__ void tma_3d(uint32_t dst, const CUtensorMap* m, uint32_t bar, int c0, int c1, int c2, uint64_t pol) {
  asm volatile("cp.async.bulk.tensor.3d.shared::cluster.global.mbarrier::complete_tx::bytes.L2::cache_hint [%0], [%1, {%3, %4, %5}], [%2], %6;"
               :: "r"(dst), "l"(m), "r"(bar), "r"(c0), "r"(c1), "r"(c2), "l"(pol) : "memory");
}
__device__ __forceinline__ void tma_store_2d(const CUtensorMap* m, uint32_t src, int c0, int c1) {
  asm volatile("cp.async.bulk.tensor.2d.global.shared::cta.bulk_group [%0, {%2, %3}], [%1];"
               :: "l"(m), "r"(src), "r"(c0), "r"(c1) : "memory");
}
__device__ __forceinline__ bool mbar_test(uint32_t bar, uint32_t parity) {
  uint32_t ok;
  asm volatile("{\n.reg .pred p;\nmbarrier.test_wait.parity.shared::cta.b64 p, [%1], %2;\nselp.u32 %0, 1, 0, p;\n}"
               : "=r"(ok) : "r"(bar), "r"(parity) : "memory");
  return ok;
}
__device__ __forceinline__ int lane_id() { int l; asm volatile("mov.u32 %0, %%laneid;" : "=r"(l)); return l; }
__device__ __forceinline__ void mbar_arrive(uint32_t bar) {
  asm volatile("mbarrier.arrive.shared::cta.b64 _, [%0];" :: "r"(bar) : "memory");
}
__device__ __forceinline__ void wg_fence()  { asm volatile("wgmma.fence.sync.aligned;" ::: "memory"); }
__device__ __forceinline__ void wg_commit() { asm volatile("wgmma.commit_group.sync.aligned;" ::: "memory"); }
template <int N> __device__ __forceinline__ void wg_wait() { asm volatile("wgmma.wait_group.sync.aligned %0;" :: "n"(N) : "memory"); }
__device__ __forceinline__ void tok_wait(int id) { asm volatile("bar.sync %0, 256;" :: "r"(id) : "memory"); }
__device__ __forceinline__ void tok_pass(int id) { asm volatile("bar.arrive %0, 256;" :: "r"(id) : "memory"); }
__device__ __forceinline__ void cluster_arrive_relaxed() { asm volatile("barrier.cluster.arrive.relaxed.aligned;" ::: "memory"); }
__device__ __forceinline__ void cluster_wait()           { asm volatile("barrier.cluster.wait.aligned;" ::: "memory"); }
__device__ __forceinline__ unsigned ld_relaxed(const unsigned* p) {
  unsigned v; asm volatile("ld.relaxed.gpu.global.u32 %0, [%1];" : "=r"(v) : "l"(p) : "memory"); return v;
}
__device__ __forceinline__ unsigned ld_acquire(const unsigned* p) {
  unsigned v; asm volatile("ld.acquire.gpu.global.u32 %0, [%1];" : "=r"(v) : "l"(p) : "memory"); return v;
}
__device__ __forceinline__ void red_release_add(unsigned* p, unsigned v) {
  asm volatile("red.release.gpu.global.add.u32 [%0], %1;" :: "l"(p), "r"(v) : "memory");
}
__device__ __forceinline__ void spin_until(const unsigned* p, unsigned target) {
  asm volatile("{\n.reg .pred P1;\n.reg .u32 cnt, v;\nmov.u32 cnt, 0;\n"
               "LAB_SPIN:\n"
               "ld.acquire.gpu.global.u32 v, [%0];\n"
               "sub.u32 v, v, %1;\n"
               "setp.ge.s32 P1, v, 0;\n"
               "@P1 bra DONE;\n"
               "nanosleep.u32 20;\n"
               "add.u32 cnt, cnt, 1;\n"
               "setp.lt.u32 P1, cnt, 4194304;\n"
               "@P1 bra LAB_SPIN;\n"
               "trap;\n"
               "DONE:\n}"
               :: "l"(p), "r"(target) : "memory");
}
__device__ __forceinline__ uint32_t desc_lo(uint32_t addr, uint32_t lbo) { return ((addr & 0x3FFFF) >> 4) | ((lbo >> 4) << 16); }
__device__ __forceinline__ uint64_t desc(uint32_t lo, uint32_t byte_off = 0, uint32_t hi = 0x40000040u) {
  uint64_t d;
  asm("mov.b64 %0, {%1, %2};" : "=l"(d) : "r"(lo + (byte_off >> 4)), "r"(hi));
  return d;
}
__device__ __forceinline__ uint32_t pack_bf16(float lo, float hi) {
  uint32_t r; asm("cvt.rn.bf16x2.f32 %0, %1, %2;" : "=r"(r) : "f"(hi), "f"(lo)); return r;
}
__device__ __forceinline__ float ex2(float x) { float r; asm("ex2.approx.ftz.f32 %0, %1;" : "=f"(r) : "f"(x)); return r; }

__device__ __forceinline__ void wgmma_ss_n192_tb1(float (&d)[96], uint64_t descA, uint64_t descB) {
  asm volatile("{\n.reg .pred p;\n"
    "setp.ne.b32 p, 1, 0;\n"
    "wgmma.mma_async.sync.aligned.m64n192k16.f32.bf16.bf16 "
    "{%0, %1, %2, %3, %4, %5, %6, %7, %8, %9, %10, %11, %12, %13, %14, %15, "
    "%16, %17, %18, %19, %20, %21, %22, %23, %24, %25, %26, %27, %28, %29, %30, %31, "
    "%32, %33, %34, %35, %36, %37, %38, %39, %40, %41, %42, %43, %44, %45, %46, %47, "
    "%48, %49, %50, %51, %52, %53, %54, %55, %56, %57, %58, %59, %60, %61, %62, %63, "
    "%64, %65, %66, %67, %68, %69, %70, %71, %72, %73, %74, %75, %76, %77, %78, %79, "
    "%80, %81, %82, %83, %84, %85, %86, %87, %88, %89, %90, %91, %92, %93, %94, %95}, "
    "%96, %97, p, 1, 1, 0, 1;\n}\n"
    : "+f"(d[0]), "+f"(d[1]), "+f"(d[2]), "+f"(d[3]), "+f"(d[4]), "+f"(d[5]), "+f"(d[6]), "+f"(d[7]),
      "+f"(d[8]), "+f"(d[9]), "+f"(d[10]), "+f"(d[11]), "+f"(d[12]), "+f"(d[13]), "+f"(d[14]), "+f"(d[15]),
      "+f"(d[16]), "+f"(d[17]), "+f"(d[18]), "+f"(d[19]), "+f"(d[20]), "+f"(d[21]), "+f"(d[22]), "+f"(d[23]),
      "+f"(d[24]), "+f"(d[25]), "+f"(d[26]), "+f"(d[27]), "+f"(d[28]), "+f"(d[29]), "+f"(d[30]), "+f"(d[31]),
      "+f"(d[32]), "+f"(d[33]), "+f"(d[34]), "+f"(d[35]), "+f"(d[36]), "+f"(d[37]), "+f"(d[38]), "+f"(d[39]),
      "+f"(d[40]), "+f"(d[41]), "+f"(d[42]), "+f"(d[43]), "+f"(d[44]), "+f"(d[45]), "+f"(d[46]), "+f"(d[47]),
      "+f"(d[48]), "+f"(d[49]), "+f"(d[50]), "+f"(d[51]), "+f"(d[52]), "+f"(d[53]), "+f"(d[54]), "+f"(d[55]),
      "+f"(d[56]), "+f"(d[57]), "+f"(d[58]), "+f"(d[59]), "+f"(d[60]), "+f"(d[61]), "+f"(d[62]), "+f"(d[63]),
      "+f"(d[64]), "+f"(d[65]), "+f"(d[66]), "+f"(d[67]), "+f"(d[68]), "+f"(d[69]), "+f"(d[70]), "+f"(d[71]),
      "+f"(d[72]), "+f"(d[73]), "+f"(d[74]), "+f"(d[75]), "+f"(d[76]), "+f"(d[77]), "+f"(d[78]), "+f"(d[79]),
      "+f"(d[80]), "+f"(d[81]), "+f"(d[82]), "+f"(d[83]), "+f"(d[84]), "+f"(d[85]), "+f"(d[86]), "+f"(d[87]),
      "+f"(d[88]), "+f"(d[89]), "+f"(d[90]), "+f"(d[91]), "+f"(d[92]), "+f"(d[93]), "+f"(d[94]), "+f"(d[95])
    : "l"(descA), "l"(descB));
}

__device__ __forceinline__ void wgmma_ss_n192_tb1_init(float (&d)[96], uint64_t descA, uint64_t descB) {
  asm volatile("{\n.reg .pred p;\n"
    "setp.ne.b32 p, 0, 0;\n"
    "wgmma.mma_async.sync.aligned.m64n192k16.f32.bf16.bf16 "
    "{%0, %1, %2, %3, %4, %5, %6, %7, %8, %9, %10, %11, %12, %13, %14, %15, "
    "%16, %17, %18, %19, %20, %21, %22, %23, %24, %25, %26, %27, %28, %29, %30, %31, "
    "%32, %33, %34, %35, %36, %37, %38, %39, %40, %41, %42, %43, %44, %45, %46, %47, "
    "%48, %49, %50, %51, %52, %53, %54, %55, %56, %57, %58, %59, %60, %61, %62, %63, "
    "%64, %65, %66, %67, %68, %69, %70, %71, %72, %73, %74, %75, %76, %77, %78, %79, "
    "%80, %81, %82, %83, %84, %85, %86, %87, %88, %89, %90, %91, %92, %93, %94, %95}, "
    "%96, %97, p, 1, 1, 0, 1;\n}\n"
    : "=f"(d[0]), "=f"(d[1]), "=f"(d[2]), "=f"(d[3]), "=f"(d[4]), "=f"(d[5]), "=f"(d[6]), "=f"(d[7]),
      "=f"(d[8]), "=f"(d[9]), "=f"(d[10]), "=f"(d[11]), "=f"(d[12]), "=f"(d[13]), "=f"(d[14]), "=f"(d[15]),
      "=f"(d[16]), "=f"(d[17]), "=f"(d[18]), "=f"(d[19]), "=f"(d[20]), "=f"(d[21]), "=f"(d[22]), "=f"(d[23]),
      "=f"(d[24]), "=f"(d[25]), "=f"(d[26]), "=f"(d[27]), "=f"(d[28]), "=f"(d[29]), "=f"(d[30]), "=f"(d[31]),
      "=f"(d[32]), "=f"(d[33]), "=f"(d[34]), "=f"(d[35]), "=f"(d[36]), "=f"(d[37]), "=f"(d[38]), "=f"(d[39]),
      "=f"(d[40]), "=f"(d[41]), "=f"(d[42]), "=f"(d[43]), "=f"(d[44]), "=f"(d[45]), "=f"(d[46]), "=f"(d[47]),
      "=f"(d[48]), "=f"(d[49]), "=f"(d[50]), "=f"(d[51]), "=f"(d[52]), "=f"(d[53]), "=f"(d[54]), "=f"(d[55]),
      "=f"(d[56]), "=f"(d[57]), "=f"(d[58]), "=f"(d[59]), "=f"(d[60]), "=f"(d[61]), "=f"(d[62]), "=f"(d[63]),
      "=f"(d[64]), "=f"(d[65]), "=f"(d[66]), "=f"(d[67]), "=f"(d[68]), "=f"(d[69]), "=f"(d[70]), "=f"(d[71]),
      "=f"(d[72]), "=f"(d[73]), "=f"(d[74]), "=f"(d[75]), "=f"(d[76]), "=f"(d[77]), "=f"(d[78]), "=f"(d[79]),
      "=f"(d[80]), "=f"(d[81]), "=f"(d[82]), "=f"(d[83]), "=f"(d[84]), "=f"(d[85]), "=f"(d[86]), "=f"(d[87]),
      "=f"(d[88]), "=f"(d[89]), "=f"(d[90]), "=f"(d[91]), "=f"(d[92]), "=f"(d[93]), "=f"(d[94]), "=f"(d[95])
    : "l"(descA), "l"(descB));
}

__device__ __forceinline__ void wgmma_ss_n160_tb1(float (&d)[80], uint64_t descA, uint64_t descB) {
  asm volatile("{\n.reg .pred p;\n"
    "setp.ne.b32 p, 1, 0;\n"
    "wgmma.mma_async.sync.aligned.m64n160k16.f32.bf16.bf16 "
    "{%0, %1, %2, %3, %4, %5, %6, %7, %8, %9, %10, %11, %12, %13, %14, %15, "
    "%16, %17, %18, %19, %20, %21, %22, %23, %24, %25, %26, %27, %28, %29, %30, %31, "
    "%32, %33, %34, %35, %36, %37, %38, %39, %40, %41, %42, %43, %44, %45, %46, %47, "
    "%48, %49, %50, %51, %52, %53, %54, %55, %56, %57, %58, %59, %60, %61, %62, %63, "
    "%64, %65, %66, %67, %68, %69, %70, %71, %72, %73, %74, %75, %76, %77, %78, %79}, "
    "%80, %81, p, 1, 1, 0, 1;\n}\n"
    : "+f"(d[0]), "+f"(d[1]), "+f"(d[2]), "+f"(d[3]), "+f"(d[4]), "+f"(d[5]), "+f"(d[6]), "+f"(d[7]),
      "+f"(d[8]), "+f"(d[9]), "+f"(d[10]), "+f"(d[11]), "+f"(d[12]), "+f"(d[13]), "+f"(d[14]), "+f"(d[15]),
      "+f"(d[16]), "+f"(d[17]), "+f"(d[18]), "+f"(d[19]), "+f"(d[20]), "+f"(d[21]), "+f"(d[22]), "+f"(d[23]),
      "+f"(d[24]), "+f"(d[25]), "+f"(d[26]), "+f"(d[27]), "+f"(d[28]), "+f"(d[29]), "+f"(d[30]), "+f"(d[31]),
      "+f"(d[32]), "+f"(d[33]), "+f"(d[34]), "+f"(d[35]), "+f"(d[36]), "+f"(d[37]), "+f"(d[38]), "+f"(d[39]),
      "+f"(d[40]), "+f"(d[41]), "+f"(d[42]), "+f"(d[43]), "+f"(d[44]), "+f"(d[45]), "+f"(d[46]), "+f"(d[47]),
      "+f"(d[48]), "+f"(d[49]), "+f"(d[50]), "+f"(d[51]), "+f"(d[52]), "+f"(d[53]), "+f"(d[54]), "+f"(d[55]),
      "+f"(d[56]), "+f"(d[57]), "+f"(d[58]), "+f"(d[59]), "+f"(d[60]), "+f"(d[61]), "+f"(d[62]), "+f"(d[63]),
      "+f"(d[64]), "+f"(d[65]), "+f"(d[66]), "+f"(d[67]), "+f"(d[68]), "+f"(d[69]), "+f"(d[70]), "+f"(d[71]),
      "+f"(d[72]), "+f"(d[73]), "+f"(d[74]), "+f"(d[75]), "+f"(d[76]), "+f"(d[77]), "+f"(d[78]), "+f"(d[79])
    : "l"(descA), "l"(descB));
}

__device__ __forceinline__ void wgmma_ss_n160_tb1_init(float (&d)[80], uint64_t descA, uint64_t descB) {
  asm volatile("{\n.reg .pred p;\n"
    "setp.ne.b32 p, 0, 0;\n"
    "wgmma.mma_async.sync.aligned.m64n160k16.f32.bf16.bf16 "
    "{%0, %1, %2, %3, %4, %5, %6, %7, %8, %9, %10, %11, %12, %13, %14, %15, "
    "%16, %17, %18, %19, %20, %21, %22, %23, %24, %25, %26, %27, %28, %29, %30, %31, "
    "%32, %33, %34, %35, %36, %37, %38, %39, %40, %41, %42, %43, %44, %45, %46, %47, "
    "%48, %49, %50, %51, %52, %53, %54, %55, %56, %57, %58, %59, %60, %61, %62, %63, "
    "%64, %65, %66, %67, %68, %69, %70, %71, %72, %73, %74, %75, %76, %77, %78, %79}, "
    "%80, %81, p, 1, 1, 0, 1;\n}\n"
    : "=f"(d[0]), "=f"(d[1]), "=f"(d[2]), "=f"(d[3]), "=f"(d[4]), "=f"(d[5]), "=f"(d[6]), "=f"(d[7]),
      "=f"(d[8]), "=f"(d[9]), "=f"(d[10]), "=f"(d[11]), "=f"(d[12]), "=f"(d[13]), "=f"(d[14]), "=f"(d[15]),
      "=f"(d[16]), "=f"(d[17]), "=f"(d[18]), "=f"(d[19]), "=f"(d[20]), "=f"(d[21]), "=f"(d[22]), "=f"(d[23]),
      "=f"(d[24]), "=f"(d[25]), "=f"(d[26]), "=f"(d[27]), "=f"(d[28]), "=f"(d[29]), "=f"(d[30]), "=f"(d[31]),
      "=f"(d[32]), "=f"(d[33]), "=f"(d[34]), "=f"(d[35]), "=f"(d[36]), "=f"(d[37]), "=f"(d[38]), "=f"(d[39]),
      "=f"(d[40]), "=f"(d[41]), "=f"(d[42]), "=f"(d[43]), "=f"(d[44]), "=f"(d[45]), "=f"(d[46]), "=f"(d[47]),
      "=f"(d[48]), "=f"(d[49]), "=f"(d[50]), "=f"(d[51]), "=f"(d[52]), "=f"(d[53]), "=f"(d[54]), "=f"(d[55]),
      "=f"(d[56]), "=f"(d[57]), "=f"(d[58]), "=f"(d[59]), "=f"(d[60]), "=f"(d[61]), "=f"(d[62]), "=f"(d[63]),
      "=f"(d[64]), "=f"(d[65]), "=f"(d[66]), "=f"(d[67]), "=f"(d[68]), "=f"(d[69]), "=f"(d[70]), "=f"(d[71]),
      "=f"(d[72]), "=f"(d[73]), "=f"(d[74]), "=f"(d[75]), "=f"(d[76]), "=f"(d[77]), "=f"(d[78]), "=f"(d[79])
    : "l"(descA), "l"(descB));
}

__device__ __forceinline__ void wgmma_rs_n96_tb0(float (&d)[48], uint32_t a0, uint32_t a1, uint32_t a2, uint32_t a3, uint64_t descB) {
  asm volatile("{\n.reg .pred p;\n"
    "setp.ne.b32 p, 1, 0;\n"
    "wgmma.mma_async.sync.aligned.m64n96k16.f32.bf16.bf16 "
    "{%0, %1, %2, %3, %4, %5, %6, %7, %8, %9, %10, %11, %12, %13, %14, %15, "
    "%16, %17, %18, %19, %20, %21, %22, %23, %24, %25, %26, %27, %28, %29, %30, %31, "
    "%32, %33, %34, %35, %36, %37, %38, %39, %40, %41, %42, %43, %44, %45, %46, %47}, "
    "{%48, %49, %50, %51}, %52, p, 1, 1, 0;\n}\n"
    : "+f"(d[0]), "+f"(d[1]), "+f"(d[2]), "+f"(d[3]), "+f"(d[4]), "+f"(d[5]), "+f"(d[6]), "+f"(d[7]),
      "+f"(d[8]), "+f"(d[9]), "+f"(d[10]), "+f"(d[11]), "+f"(d[12]), "+f"(d[13]), "+f"(d[14]), "+f"(d[15]),
      "+f"(d[16]), "+f"(d[17]), "+f"(d[18]), "+f"(d[19]), "+f"(d[20]), "+f"(d[21]), "+f"(d[22]), "+f"(d[23]),
      "+f"(d[24]), "+f"(d[25]), "+f"(d[26]), "+f"(d[27]), "+f"(d[28]), "+f"(d[29]), "+f"(d[30]), "+f"(d[31]),
      "+f"(d[32]), "+f"(d[33]), "+f"(d[34]), "+f"(d[35]), "+f"(d[36]), "+f"(d[37]), "+f"(d[38]), "+f"(d[39]),
      "+f"(d[40]), "+f"(d[41]), "+f"(d[42]), "+f"(d[43]), "+f"(d[44]), "+f"(d[45]), "+f"(d[46]), "+f"(d[47])
    : "r"(a0), "r"(a1), "r"(a2), "r"(a3), "l"(descB));
}

__device__ __forceinline__ void wgmma_rs_n96_tb0_init(float (&d)[48], uint32_t a0, uint32_t a1, uint32_t a2, uint32_t a3, uint64_t descB) {
  asm volatile("{\n.reg .pred p;\n"
    "setp.ne.b32 p, 0, 0;\n"
    "wgmma.mma_async.sync.aligned.m64n96k16.f32.bf16.bf16 "
    "{%0, %1, %2, %3, %4, %5, %6, %7, %8, %9, %10, %11, %12, %13, %14, %15, "
    "%16, %17, %18, %19, %20, %21, %22, %23, %24, %25, %26, %27, %28, %29, %30, %31, "
    "%32, %33, %34, %35, %36, %37, %38, %39, %40, %41, %42, %43, %44, %45, %46, %47}, "
    "{%48, %49, %50, %51}, %52, p, 1, 1, 0;\n}\n"
    : "=f"(d[0]), "=f"(d[1]), "=f"(d[2]), "=f"(d[3]), "=f"(d[4]), "=f"(d[5]), "=f"(d[6]), "=f"(d[7]),
      "=f"(d[8]), "=f"(d[9]), "=f"(d[10]), "=f"(d[11]), "=f"(d[12]), "=f"(d[13]), "=f"(d[14]), "=f"(d[15]),
      "=f"(d[16]), "=f"(d[17]), "=f"(d[18]), "=f"(d[19]), "=f"(d[20]), "=f"(d[21]), "=f"(d[22]), "=f"(d[23]),
      "=f"(d[24]), "=f"(d[25]), "=f"(d[26]), "=f"(d[27]), "=f"(d[28]), "=f"(d[29]), "=f"(d[30]), "=f"(d[31]),
      "=f"(d[32]), "=f"(d[33]), "=f"(d[34]), "=f"(d[35]), "=f"(d[36]), "=f"(d[37]), "=f"(d[38]), "=f"(d[39]),
      "=f"(d[40]), "=f"(d[41]), "=f"(d[42]), "=f"(d[43]), "=f"(d[44]), "=f"(d[45]), "=f"(d[46]), "=f"(d[47])
    : "r"(a0), "r"(a1), "r"(a2), "r"(a3), "l"(descB));
}

__device__ __forceinline__ void wgmma_rs_n128_tb1(float (&d)[64], uint32_t a0, uint32_t a1, uint32_t a2, uint32_t a3, uint64_t descB) {
  asm volatile("{\n.reg .pred p;\n"
    "setp.ne.b32 p, 1, 0;\n"
    "wgmma.mma_async.sync.aligned.m64n128k16.f32.bf16.bf16 "
    "{%0, %1, %2, %3, %4, %5, %6, %7, %8, %9, %10, %11, %12, %13, %14, %15, "
    "%16, %17, %18, %19, %20, %21, %22, %23, %24, %25, %26, %27, %28, %29, %30, %31, "
    "%32, %33, %34, %35, %36, %37, %38, %39, %40, %41, %42, %43, %44, %45, %46, %47, "
    "%48, %49, %50, %51, %52, %53, %54, %55, %56, %57, %58, %59, %60, %61, %62, %63}, "
    "{%64, %65, %66, %67}, %68, p, 1, 1, 1;\n}\n"
    : "+f"(d[0]), "+f"(d[1]), "+f"(d[2]), "+f"(d[3]), "+f"(d[4]), "+f"(d[5]), "+f"(d[6]), "+f"(d[7]),
      "+f"(d[8]), "+f"(d[9]), "+f"(d[10]), "+f"(d[11]), "+f"(d[12]), "+f"(d[13]), "+f"(d[14]), "+f"(d[15]),
      "+f"(d[16]), "+f"(d[17]), "+f"(d[18]), "+f"(d[19]), "+f"(d[20]), "+f"(d[21]), "+f"(d[22]), "+f"(d[23]),
      "+f"(d[24]), "+f"(d[25]), "+f"(d[26]), "+f"(d[27]), "+f"(d[28]), "+f"(d[29]), "+f"(d[30]), "+f"(d[31]),
      "+f"(d[32]), "+f"(d[33]), "+f"(d[34]), "+f"(d[35]), "+f"(d[36]), "+f"(d[37]), "+f"(d[38]), "+f"(d[39]),
      "+f"(d[40]), "+f"(d[41]), "+f"(d[42]), "+f"(d[43]), "+f"(d[44]), "+f"(d[45]), "+f"(d[46]), "+f"(d[47]),
      "+f"(d[48]), "+f"(d[49]), "+f"(d[50]), "+f"(d[51]), "+f"(d[52]), "+f"(d[53]), "+f"(d[54]), "+f"(d[55]),
      "+f"(d[56]), "+f"(d[57]), "+f"(d[58]), "+f"(d[59]), "+f"(d[60]), "+f"(d[61]), "+f"(d[62]), "+f"(d[63])
    : "r"(a0), "r"(a1), "r"(a2), "r"(a3), "l"(descB));
}

__device__ __forceinline__ void wgmma_rs_n128_tb1_init(float (&d)[64], uint32_t a0, uint32_t a1, uint32_t a2, uint32_t a3, uint64_t descB) {
  asm volatile("{\n.reg .pred p;\n"
    "setp.ne.b32 p, 0, 0;\n"
    "wgmma.mma_async.sync.aligned.m64n128k16.f32.bf16.bf16 "
    "{%0, %1, %2, %3, %4, %5, %6, %7, %8, %9, %10, %11, %12, %13, %14, %15, "
    "%16, %17, %18, %19, %20, %21, %22, %23, %24, %25, %26, %27, %28, %29, %30, %31, "
    "%32, %33, %34, %35, %36, %37, %38, %39, %40, %41, %42, %43, %44, %45, %46, %47, "
    "%48, %49, %50, %51, %52, %53, %54, %55, %56, %57, %58, %59, %60, %61, %62, %63}, "
    "{%64, %65, %66, %67}, %68, p, 1, 1, 1;\n}\n"
    : "=f"(d[0]), "=f"(d[1]), "=f"(d[2]), "=f"(d[3]), "=f"(d[4]), "=f"(d[5]), "=f"(d[6]), "=f"(d[7]),
      "=f"(d[8]), "=f"(d[9]), "=f"(d[10]), "=f"(d[11]), "=f"(d[12]), "=f"(d[13]), "=f"(d[14]), "=f"(d[15]),
      "=f"(d[16]), "=f"(d[17]), "=f"(d[18]), "=f"(d[19]), "=f"(d[20]), "=f"(d[21]), "=f"(d[22]), "=f"(d[23]),
      "=f"(d[24]), "=f"(d[25]), "=f"(d[26]), "=f"(d[27]), "=f"(d[28]), "=f"(d[29]), "=f"(d[30]), "=f"(d[31]),
      "=f"(d[32]), "=f"(d[33]), "=f"(d[34]), "=f"(d[35]), "=f"(d[36]), "=f"(d[37]), "=f"(d[38]), "=f"(d[39]),
      "=f"(d[40]), "=f"(d[41]), "=f"(d[42]), "=f"(d[43]), "=f"(d[44]), "=f"(d[45]), "=f"(d[46]), "=f"(d[47]),
      "=f"(d[48]), "=f"(d[49]), "=f"(d[50]), "=f"(d[51]), "=f"(d[52]), "=f"(d[53]), "=f"(d[54]), "=f"(d[55]),
      "=f"(d[56]), "=f"(d[57]), "=f"(d[58]), "=f"(d[59]), "=f"(d[60]), "=f"(d[61]), "=f"(d[62]), "=f"(d[63])
    : "r"(a0), "r"(a1), "r"(a2), "r"(a3), "l"(descB));
}

__device__ __forceinline__ void wgmma_rs_n64_tb1(float (&d)[32], uint32_t a0, uint32_t a1, uint32_t a2, uint32_t a3, uint64_t descB) {
  asm volatile("{\n.reg .pred p;\n"
    "setp.ne.b32 p, 1, 0;\n"
    "wgmma.mma_async.sync.aligned.m64n64k16.f32.bf16.bf16 "
    "{%0, %1, %2, %3, %4, %5, %6, %7, %8, %9, %10, %11, %12, %13, %14, %15, "
    "%16, %17, %18, %19, %20, %21, %22, %23, %24, %25, %26, %27, %28, %29, %30, %31}, "
    "{%32, %33, %34, %35}, %36, p, 1, 1, 1;\n}\n"
    : "+f"(d[0]), "+f"(d[1]), "+f"(d[2]), "+f"(d[3]), "+f"(d[4]), "+f"(d[5]), "+f"(d[6]), "+f"(d[7]),
      "+f"(d[8]), "+f"(d[9]), "+f"(d[10]), "+f"(d[11]), "+f"(d[12]), "+f"(d[13]), "+f"(d[14]), "+f"(d[15]),
      "+f"(d[16]), "+f"(d[17]), "+f"(d[18]), "+f"(d[19]), "+f"(d[20]), "+f"(d[21]), "+f"(d[22]), "+f"(d[23]),
      "+f"(d[24]), "+f"(d[25]), "+f"(d[26]), "+f"(d[27]), "+f"(d[28]), "+f"(d[29]), "+f"(d[30]), "+f"(d[31])
    : "r"(a0), "r"(a1), "r"(a2), "r"(a3), "l"(descB));
}

__device__ __forceinline__ void wgmma_rs_n64_tb1_init(float (&d)[32], uint32_t a0, uint32_t a1, uint32_t a2, uint32_t a3, uint64_t descB) {
  asm volatile("{\n.reg .pred p;\n"
    "setp.ne.b32 p, 0, 0;\n"
    "wgmma.mma_async.sync.aligned.m64n64k16.f32.bf16.bf16 "
    "{%0, %1, %2, %3, %4, %5, %6, %7, %8, %9, %10, %11, %12, %13, %14, %15, "
    "%16, %17, %18, %19, %20, %21, %22, %23, %24, %25, %26, %27, %28, %29, %30, %31}, "
    "{%32, %33, %34, %35}, %36, p, 1, 1, 1;\n}\n"
    : "=f"(d[0]), "=f"(d[1]), "=f"(d[2]), "=f"(d[3]), "=f"(d[4]), "=f"(d[5]), "=f"(d[6]), "=f"(d[7]),
      "=f"(d[8]), "=f"(d[9]), "=f"(d[10]), "=f"(d[11]), "=f"(d[12]), "=f"(d[13]), "=f"(d[14]), "=f"(d[15]),
      "=f"(d[16]), "=f"(d[17]), "=f"(d[18]), "=f"(d[19]), "=f"(d[20]), "=f"(d[21]), "=f"(d[22]), "=f"(d[23]),
      "=f"(d[24]), "=f"(d[25]), "=f"(d[26]), "=f"(d[27]), "=f"(d[28]), "=f"(d[29]), "=f"(d[30]), "=f"(d[31])
    : "r"(a0), "r"(a1), "r"(a2), "r"(a3), "l"(descB));
}

template <int V> struct Int { static constexpr int value = V; };

struct Ring {
  uint32_t u;
  __device__ __forceinline__ uint32_t slot()  const { return u & (NSLOT - 1); }
  __device__ __forceinline__ uint32_t phase() const { return (u >> 2) & 1; }
  __device__ __forceinline__ uint32_t full(uint32_t full0)   const { return full0 + 8 * slot(); }
  __device__ __forceinline__ uint32_t empty(uint32_t full0)  const { return full0 + 8 * NSLOT + 8 * slot(); }
  __device__ __forceinline__ uint32_t addr(uint32_t ring)    const { return ring + slot() * SLOT_BYTES; }
  __device__ __forceinline__ Ring operator+(uint32_t d) const { return Ring{u + d}; }
};

__device__ __forceinline__ void softmax96(float (&s)[48], uint32_t (&p)[24], float& r0, float& r1) {
  const float c = 0.07216878364870322f * 1.4426950408889634f;
  float a0[6], a1[6];
#pragma unroll
  for (int j = 0; j < 6; j++) {
    a0[j] = fmaxf(fmaxf(s[8 * j], s[8 * j + 1]), fmaxf(s[8 * j + 4], s[8 * j + 5]));
    a1[j] = fmaxf(fmaxf(s[8 * j + 2], s[8 * j + 3]), fmaxf(s[8 * j + 6], s[8 * j + 7]));
  }
  float m0 = fmaxf(fmaxf(fmaxf(a0[0], a0[1]), fmaxf(a0[2], a0[3])), fmaxf(a0[4], a0[5]));
  float m1 = fmaxf(fmaxf(fmaxf(a1[0], a1[1]), fmaxf(a1[2], a1[3])), fmaxf(a1[4], a1[5]));
  m0 = fmaxf(m0, __shfl_xor_sync(0xffffffffu, m0, 1));
  m1 = fmaxf(m1, __shfl_xor_sync(0xffffffffu, m1, 1));
  m0 = fmaxf(m0, __shfl_xor_sync(0xffffffffu, m0, 2));
  m1 = fmaxf(m1, __shfl_xor_sync(0xffffffffu, m1, 2));
  const float b0 = -m0 * c, b1 = -m1 * c;
  float l0 = 0.f, l1 = 0.f;
#pragma unroll
  for (int j = 0; j < 12; j++) {
    const float e0 = ex2(fmaf(s[4 * j],     c, b0)), e1 = ex2(fmaf(s[4 * j + 1], c, b0));
    const float e2 = ex2(fmaf(s[4 * j + 2], c, b1)), e3 = ex2(fmaf(s[4 * j + 3], c, b1));
    l0 += e0 + e1;
    l1 += e2 + e3;
    p[2 * j]     = pack_bf16(e0, e1);
    p[2 * j + 1] = pack_bf16(e2, e3);
  }
  l0 += __shfl_xor_sync(0xffffffffu, l0, 1);
  l1 += __shfl_xor_sync(0xffffffffu, l1, 1);
  l0 += __shfl_xor_sync(0xffffffffu, l0, 2);
  l1 += __shfl_xor_sync(0xffffffffu, l1, 2);
  asm("rcp.approx.ftz.f32 %0, %1;" : "=f"(r0) : "f"(l0));
  asm("rcp.approx.ftz.f32 %0, %1;" : "=f"(r1) : "f"(l1));
}

template <bool INIT>
__device__ __forceinline__ void qk_mma(float (&s)[48], const uint32_t (&qf)[48], uint32_t box0, uint32_t box1, uint32_t box2, int pass_id) {
  const uint32_t d0 = desc_lo(box0, 16), d1 = desc_lo(box1, 16), d2 = desc_lo(box2, 16);
  if (INIT) wgmma_rs_n96_tb0_init(s, qf[0], qf[1], qf[2], qf[3], desc(d0));
  else      wgmma_rs_n96_tb0(s, qf[0], qf[1], qf[2], qf[3], desc(d0));
#pragma unroll
  for (int k = 1; k < 12; k++) {
    wgmma_rs_n96_tb0(s, qf[4 * k], qf[4 * k + 1], qf[4 * k + 2], qf[4 * k + 3], desc(k < 4 ? d0 : k < 8 ? d1 : d2, (k & 3) * 32));
  }
  tok_pass(pass_id);
}
template <bool INIT>
__device__ __forceinline__ void pv_mma(float (&o)[96], const uint32_t (&pf)[24], uint32_t box01, uint32_t box2, int pass_id) {
  float (&oa)[64] = *reinterpret_cast<float (*)[64]>(&o[0]);
  float (&ob)[32] = *reinterpret_cast<float (*)[32]>(&o[64]);
  const uint32_t da = desc_lo(box01, 12288), db = desc_lo(box2, 12288);
  if (INIT) { wgmma_rs_n128_tb1_init(oa, pf[0], pf[1], pf[2], pf[3], desc(da)); wgmma_rs_n64_tb1_init(ob, pf[0], pf[1], pf[2], pf[3], desc(db)); }
  else      { wgmma_rs_n128_tb1(oa, pf[0], pf[1], pf[2], pf[3], desc(da));      wgmma_rs_n64_tb1(ob, pf[0], pf[1], pf[2], pf[3], desc(db)); }
#pragma unroll
  for (int k = 1; k < 6; k++) {
    wgmma_rs_n128_tb1(oa, pf[4 * k], pf[4 * k + 1], pf[4 * k + 2], pf[4 * k + 3], desc(da, k * 2048));
    wgmma_rs_n64_tb1(ob, pf[4 * k], pf[4 * k + 1], pf[4 * k + 2], pf[4 * k + 3], desc(db, k * 2048));
  }
  tok_pass(pass_id);
}

__global__ void __cluster_dims__(2, 1, 1) __launch_bounds__(NTHREADS, 1)
fused_attn_kernel(const __grid_constant__ Params prm, __nv_bfloat16* __restrict__ out) {
  extern __shared__ uint8_t smem_raw[];
  __shared__ uint64_t s_bars[3 * NSLOT + 10];
  __shared__ uint32_t s_dummy[64];
  __shared__ volatile uint32_t s_prog;

  const uint32_t ring = (smem_u32(smem_raw) + 1023) & ~1023u;
  const uint32_t stg  = ring + NSLOT * SLOT_BYTES;
  const uint32_t full0 = smem_u32(&s_bars[0]);
  const uint32_t o_done  = full0 + 24 * NSLOT;
  const uint32_t o_ready = o_done + 48;

  const int tid = threadIdx.x, lane = tid & 31;
  const int warp = __shfl_sync(0xffffffffu, tid >> 5, 0);
  const int rank = blockIdx.x & 1, cl = logical_cluster(blockIdx.x >> 1), cta = 2 * cl + rank;
  const int grp = cl >> 3, prob = grp >> 2, bp = grp & 3, j8 = cl & 7;
  const int split = j8 >> 1;

  if (tid == 13 * 32) {
    asm volatile("prefetch.tensormap [%0];" :: "l"(&prm.wq[prob]) : "memory");
    asm volatile("prefetch.tensormap [%0];" :: "l"(&prm.x1[prob]) : "memory");
    asm volatile("prefetch.tensormap [%0];" :: "l"(&prm.x[prob]) : "memory");
  }
  if (tid == 12 * 32) {
#pragma unroll
    for (int s = 0; s < NSLOT; s++) { mbar_init(full0 + 8 * s, 1); mbar_init(full0 + 8 * NSLOT + 8 * s, 3); mbar_init(full0 + 16 * NSLOT + 8 * s, 3); }
    for (int s = 0; s < 6; s++) mbar_init(o_done + 8 * s, 12);
    for (int s = 0; s < 4; s++) mbar_init(o_ready + 8 * s, 1);
    s_prog = NSLOT;
    asm volatile("fence.mbarrier_init.release.cluster;" ::: "memory");
  }
  __syncthreads();
  cluster_arrive_relaxed();
  if (tid == 12 * 32) {
    const int h = 2 * j8 + rank;
    const uint64_t pol = policy_evict_first();
#pragma unroll
    for (int s = 0; s < NSLOT; s++) {
      mbar_expect_tx(full0 + 8 * s, SLOT_BYTES);
      tma_2d_nohint(ring + s * SLOT_BYTES, &prm.x1[prob], full0 + 8 * s, 64 * s, 192 * bp);
      tma_3d(ring + s * SLOT_BYTES + B_OFF, &prm.wq[prob], full0 + 8 * s, 0, 64 * s, 3 * h, pol);
    }
  }
  __syncwarp();
  cluster_wait();

  if (warp >= 12) {
    asm volatile("setmaxnreg.dec.sync.aligned.u32 32;");
    if (warp == 12) {
      if (lane == 0) {
        Ring r{0};
        const uint64_t pol_s = policy_evict_first();
        const int ncol0 = 320 * (j8 & 1);
#pragma unroll 1
        for (int w = 0; w < 2; w++) {
          const int h = 16 * w + 2 * j8 + rank;
#pragma unroll 1
          for (int ks = 0; ks < 10; ks++) {
            const uint32_t fb = r.full(full0), sl = r.addr(ring);
            if (r.u >= NSLOT) {
              mbar_wait(r.empty(full0), r.phase() ^ 1);
              mbar_expect_tx(fb, SLOT_BYTES);
              s_prog = r.u;
              tma_3d(sl + B_OFF, &prm.wq[prob], fb, 0, 64 * ks, 3 * h, pol_s);
              mbar_wait(r.empty(full0) + 8 * NSLOT, r.phase() ^ 1);
              tma_2d_mc(sl + rank * 12288, &prm.x[prob], fb, 64 * ks, 192 * bp + 96 * rank);
            }
            r.u++;
          }
#pragma unroll 1
          for (int t = 0; t < 3; t++) {
            const uint32_t fb = r.full(full0), sl = r.addr(ring);
            const int row0 = ((2 * bp) * 32 + h) * 96, row1 = row0 + 32 * 96;
            mbar_wait(r.empty(full0), r.phase() ^ 1);
            mbar_expect_tx(fb, SLOT_BYTES);
            s_prog = r.u;
            if (t == 0) {
              tma_3d(sl,         &prm.k[prob],  fb, 0, row0, 0, pol_s);
              tma_3d(sl + 36864, &prm.k1[prob], fb, 0, row1, 0, pol_s);
            } else if (t == 1) {
              tma_3d(sl,         &prm.k1[prob], fb, 0, row1, 1, pol_s);
              tma_3d(sl + 12288, &prm.k1[prob], fb, 0, row1, 2, pol_s);
              tma_3d(sl + 24576, &prm.v1[prob], fb, 0, row0, 0, pol_s);
              tma_3d(sl + 36864, &prm.v1[prob], fb, 0, row0, 1, pol_s);
            } else {
              tma_3d(sl,         &prm.v1[prob], fb, 0, row0, 2, pol_s);
              tma_3d(sl + 12288, &prm.v[prob],  fb, 0, row1, 0, pol_s);
            }
            mbar_wait(r.empty(full0) + 8 * NSLOT, r.phase() ^ 1);
            r.u++;
          }
        }
#pragma unroll 1
        for (int i = 0; i < 24; i++) {
          const int h = i < 12 ? 4 * split + i / 3 : 16 + 4 * split + (i & 3);
          const int c = i < 12 ? i % 3 : (i - 12) >> 2;
          const uint32_t fb = r.full(full0), sl = r.addr(ring);
          const int k0 = h * 192 + c * 64;
          mbar_wait(r.empty(full0), r.phase() ^ 1);
          mbar_expect_tx(fb, SLOT_BYTES);
          s_prog = r.u;
          tma_2d(sl + B_OFF,         &prm.wo[prob],   fb, ncol0 + 192 * rank,      k0, pol_s);
          tma_2d(sl + B_OFF + 8192,  &prm.wo[prob],   fb, ncol0 + 192 * rank + 64, k0, pol_s);
          tma_2d(sl + B_OFF + 16384, &prm.wo[prob],   fb, ncol0 + 128, k0, pol_s);
          if (i == 0 || (i >= 12 && (i & 3) == 0)) {
            mbar_wait(o_ready + 8 * (i == 0 ? 0 : (i >> 2) - 2), 0);
          }
          mbar_wait(r.empty(full0) + 8 * NSLOT, r.phase() ^ 1);
          tma_2d_mc(sl + rank * 12288, &prm.o_ld, fb, k0, prob * 768 + 192 * bp + 96 * rank);
          r.u++;
        }
      }
    } else if (warp == 13) {
      {
        const unsigned obase = 3u * ld_relaxed(&prm.epoch[cta]);
        uint32_t pub = 0, wat = 0;
#pragma unroll 1
        for (int it = 0; it < (1 << 22) && (pub < 6 || wat < 4); it++) {
          if (pub < 6 && mbar_test(o_done + 8 * pub, 0)) {
            uint32_t n = 1;
            while ((pub + n) % 3 != 0 && mbar_test(o_done + 8 * (pub + n), 0)) n++;
            if (lane == 0) {
              asm volatile("red.relaxed.gpu.global.add.u32 [%0], %1;"
                           :: "l"(&prm.ready[grp * 32 + 16 * (pub >= 3) + 2 * j8 + rank]), "r"(n) : "memory");
            }
            __syncwarp();
            pub += n;
          } else if (wat < 4 && pub > wat + 2) {
            const unsigned tgt = obase + (wat == 0 ? 3u : wat);
            const unsigned a = ld_acquire(&prm.ready[grp * 32 + (wat == 0 ? 0 : 16) + 4 * split + (lane & 3)]);
            if (__all_sync(0xffffffffu, (int)(a - tgt) >= 0)) {
              if (lane == 0) {
                asm volatile("fence.proxy.async;" ::: "memory");
                mbar_arrive(o_ready + 8 * wat);
              }
              __syncwarp();
              wat++;
            }
          } else {
            mbar_wait(o_done + 8 * pub, 0);
          }
        }
      }
    } else {
      const int h0 = 2 * j8 + rank;
      const uint8_t* wqp = prm.wqptr[prob];
      auto addr_of = [&](int n) -> const uint8_t* {
        if (n < 9 || (n >= 45 && n < 60)) {
          const bool second = n >= 45;
          const int i = (second ? n - 45 : n + 6) * 32 + lane;
          const int ks = i / 48, rem = i - ks * 48;
          return wqp + (size_t)(64 * ks + 16 * bp + rem / 3) * 12288 + (h0 + (second ? 16 : 0)) * 384 + (rem % 3) * 128;
        }
        const bool second = n >= 60;
        const int m = second ? n - 60 : n - 9, tile = m / 9;
        const uint8_t* base = (tile < 2) ? prm.kptr[prob] : prm.vptr[prob];
        return base + (size_t)((2 * bp + (tile & 1)) * 32 + h0 + (second ? 16 : 0)) * KV_BYTES + (m - 9 * tile) * 4096 + lane * 128;
      };
      auto use_of = [&](int n) -> int {
        if (n < 9)  return ((n + 6) * 32) / 48;
        if (n < 45) { const int t = (n - 9) / 9; return 10 + (t < 2 ? 0 : t - 1); }
        if (n < 60) return 13 + ((n - 45) * 32) / 48;
        const int t = (n - 60) / 9;
        return 23 + (t < 2 ? 0 : t - 1);
      };
      auto release_of = [&](int n) -> int {
        if (n < 9)  return 0;
        if (n < 45) return PF_R0 + ((n - 9) * (PF_R1 - PF_R0)) / 36;
        if (n < 60) return PF_R1 + ((n - 45) * (PF_R2 - PF_R1)) / 15;
        return PF_R2 + ((n - 60) * (PF_R3 - PF_R2)) / 36;
      };
      const uint32_t dummy = smem_u32(&s_dummy[tid & 63]);
#pragma unroll 1
      for (int n = warp - 14; n < 96; n += 2) {
        const int u = use_of(n), rel = release_of(n);
        int guard = 0;
        while ((int)s_prog < rel && ++guard < (1 << 20)) __nanosleep(100);
        if ((int)s_prog < u)
          asm volatile("cp.async.ca.shared.global.L2::128B [%0], [%1], 4;" :: "r"(dummy), "l"(addr_of(n)) : "memory");
        asm volatile("cp.async.commit_group;" ::: "memory");
        asm volatile("cp.async.wait_group %0;" :: "n"(PF_WIN) : "memory");
      }
      asm volatile("cp.async.wait_group 0;" ::: "memory");
    }
  } else {
    asm volatile("setmaxnreg.inc.sync.aligned.u32 160;");
    const int wg = warp >> 2, wq4 = warp & 3;
    const bool elected = wq4 == 0 && lane_id() == 0;
    const uint32_t descA0 = desc_lo(ring + wg * 8192, 16), descB0 = desc_lo(ring + B_OFF, 8192);
    Ring r{0};
    uint32_t pend[32];
    const uint32_t wstg = stg + warp * 2048;
    auto stg_acquire = [&]() {
      if (lane_id() == 0) asm volatile("cp.async.bulk.wait_group.read 0;" ::: "memory");
      __syncwarp();
    };
    auto stage_in = [&](const uint32_t* v) {
      stg_acquire();
      const int lane = lane_id(), r8 = lane & 7;
      const uint32_t st_base = wstg + (((lane >> 3) & 1) * 8 + r8) * 128;
#pragma unroll
      for (int jj = 0; jj < 4; jj++) {
        const uint32_t addr = st_base + (((2 * jj + (lane >> 4)) ^ r8) << 4);
        asm volatile("stmatrix.sync.aligned.m8n8.x4.shared.b16 [%0], {%1, %2, %3, %4};"
                     :: "r"(addr), "r"(v[4 * jj]), "r"(v[4 * jj + 1]), "r"(v[4 * jj + 2]), "r"(v[4 * jj + 3]) : "memory");
      }
    };
    auto send = [&](int wv, int box) {
      asm volatile("fence.proxy.async.shared::cta;" ::: "memory");
      __syncwarp();
      if (lane_id() == 0) {
        tma_store_2d(&prm.o_st, wstg, (16 * wv + 2 * j8 + rank) * 192 + 64 * box, prob * 768 + 192 * bp + 16 * warp);
        asm volatile("cp.async.bulk.commit_group;" ::: "memory");
      }
    };
    auto landed = [&](int ev, auto pending) {
      if (lane_id() == 0) {
        asm volatile("cp.async.bulk.wait_group %0;" :: "n"(decltype(pending)::value) : "memory");
        mbar_arrive(o_done + 8 * ev);
      }
    };

#pragma unroll 1
    for (int w = 0; w < 2; w++) {
      uint32_t qf[48];
      {
        float acc[96];
        {
          const uint32_t da = descA0 + r.slot() * (SLOT_BYTES >> 4), db = descB0 + r.slot() * (SLOT_BYTES >> 4);
          mbar_wait(r.full(full0), r.phase());
          if (w > 0) { if (wg == 0) tok_wait(14); else if (wg == 2) tok_wait(15); }
          wg_fence();
          wgmma_ss_n192_tb1_init(acc, desc(da), desc(db));
#pragma unroll
          for (int k = 1; k < 4; k++) wgmma_ss_n192_tb1(acc, desc(da, k * 32), desc(db, k * 2048));
          wg_commit();
          if (w > 0 && wg == 0) tok_pass(15);
          if (w > 0) send(0, 0);
          r.u++;
        }
#pragma unroll 1
        for (int ks = 1; ks < 8; ks++) {
          const uint32_t da = descA0 + r.slot() * (SLOT_BYTES >> 4), db = descB0 + r.slot() * (SLOT_BYTES >> 4);
          mbar_wait(r.full(full0), r.phase());
          wg_fence();
          wgmma_ss_n192_tb1(acc, desc(da), desc(db));
          wg_commit();
          wg_wait<1>();
          if (elected) mbar_arrive_both(Ring{r.u - 1}.empty(full0), rank ^ 1);
#pragma unroll
          for (int k = 1; k < 4; k++) wgmma_ss_n192_tb1(acc, desc(da, k * 32), desc(db, k * 2048));
          wg_commit();
          if (w > 0) {
            if (ks == FL_B1)      { stage_in(pend);      send(0, 1); }
            else if (ks == FL_B2) { stage_in(pend + 16); send(0, 2); }
            else if (ks == FL_LD) { landed(0, Int<0>{}); landed(1, Int<0>{}); landed(2, Int<0>{}); }
          }
          r.u++;
        }
        {
          const Ring r8 = r, r9 = r + 1;
          r.u += 2;
          wg_wait<0>();
          if (elected) mbar_arrive_both(Ring{r8.u - 1}.empty(full0), rank ^ 1);
          mbar_wait(r8.full(full0), r8.phase());
          mbar_wait(r9.full(full0), r9.phase());
          if (wg != 1) tok_wait(wg == 0 ? 4 : 5);
          const uint32_t da8 = descA0 + r8.slot() * (SLOT_BYTES >> 4), db8 = descB0 + r8.slot() * (SLOT_BYTES >> 4);
          const uint32_t da9 = descA0 + r9.slot() * (SLOT_BYTES >> 4), db9 = descB0 + r9.slot() * (SLOT_BYTES >> 4);
          wg_fence();
#pragma unroll
          for (int k = 0; k < 4; k++) wgmma_ss_n192_tb1(acc, desc(da8, k * 32), desc(db8, k * 2048));
          wg_commit();
#pragma unroll
          for (int k = 0; k < 4; k++) wgmma_ss_n192_tb1(acc, desc(da9, k * 32), desc(db9, k * 2048));
          wg_commit();
          if (wg != 2) tok_pass(wg == 1 ? 4 : 5);
          wg_wait<1>();
          if (elected) mbar_arrive_both(r8.empty(full0), rank ^ 1);
          mbar_wait(r.full(full0), r.phase());
          if (wg == 2) mbar_wait((r + 1).full(full0), (r + 1).phase());
          wg_wait<0>();
          if (elected) mbar_arrive_both(r9.empty(full0), rank ^ 1);
        }
        stg_acquire();
        const int lane = lane_id();
#pragma unroll
        for (int i = 0; i < 4; i++)
          asm volatile("st.shared.v4.u32 [%0], {%1, %2, %3, %4};"
                       :: "r"(wstg + i * 512 + lane * 16),
                          "r"(pack_bf16(acc[64 + 8 * i], acc[65 + 8 * i])), "r"(pack_bf16(acc[66 + 8 * i], acc[67 + 8 * i])),
                          "r"(pack_bf16(acc[68 + 8 * i], acc[69 + 8 * i])), "r"(pack_bf16(acc[70 + 8 * i], acc[71 + 8 * i])) : "memory");
#pragma unroll
        for (int i = 0; i < 32; i++) qf[i] = pack_bf16(acc[2 * i], acc[2 * i + 1]);
        asm volatile("" ::: "memory");
#pragma unroll
        for (int i = 0; i < 4; i++)
          asm volatile("ld.shared.v4.u32 {%0, %1, %2, %3}, [%4];"
                       : "=r"(qf[32 + 4 * i]), "=r"(qf[33 + 4 * i]), "=r"(qf[34 + 4 * i]), "=r"(qf[35 + 4 * i])
                       : "r"(wstg + i * 512 + lane * 16) : "memory");
      }
      const Ring rX = r, rY = r + 1, rZ = r + 2;
      r.u += 3;
      uint32_t pf[24];
      float rinv0, rinv1;
      bool z_ready;
      const uint32_t aX = rX.addr(ring), aY = rY.addr(ring), aZ = rZ.addr(ring);
      {
        float s[48];
        if (wg != 1) tok_wait(wg == 0 ? 7 : 9);
        wg_fence();
        qk_mma<true>(s, qf, wg == 2 ? aX + 36864 : aX, wg == 2 ? aY : aX + 12288, wg == 2 ? aY + 12288 : aX + 24576, wg == 1 ? 7 : wg == 0 ? 8 : 10);
        wg_commit();
        if (wg != 2) mbar_wait(rY.full(full0), rY.phase());
        wg_wait<0>();
        if (wg == 1) {
          if (wq4 < 2) {
#pragma unroll
            for (int i = 0; i < 48; i++) qf[i] = 0u;
          } else {
#pragma unroll
            for (int i = 0; i < 48; i++) s[i] = 0.f;
          }
          tok_wait(8);
          wg_fence();
          qk_mma<false>(s, qf, aX + 36864, aY, aY + 12288, 9);
          wg_commit();
          wg_wait<0>();
        }
        if (elected) { mbar_arrive_both(rX.empty(full0), rank ^ 1); if (wg == 2) mbar_arrive_both(rY.empty(full0), rank ^ 1); }
        __syncwarp();
        z_ready = mbar_test(rZ.full(full0), rZ.phase());
        softmax96(s, pf, rinv0, rinv1);
      }
      float o[96];
      {
        if (!__all_sync(0xffffffffu, z_ready)) mbar_wait(rZ.full(full0), rZ.phase());
        tok_wait(wg == 0 ? 10 : wg == 1 ? 11 : 12);
        wg_fence();
        pv_mma<true>(o, pf, wg == 2 ? aZ + 12288 : aY + 24576, wg == 2 ? aZ + 36864 : aZ, wg == 0 ? 11 : wg == 1 ? 12 : 13);
        wg_commit();
        wg_wait<0>();
        if (wg == 1) {
          if (elected) mbar_arrive_both(rY.empty(full0), rank ^ 1);
          if (wq4 < 2) {
#pragma unroll
            for (int i = 0; i < 24; i++) pf[i] = 0u;
          } else {
#pragma unroll
            for (int i = 0; i < 96; i++) o[i] = 0.f;
          }
          tok_wait(13);
          wg_fence();
          pv_mma<false>(o, pf, aZ + 12288, aZ + 36864, 14);
          wg_commit();
          wg_wait<0>();
        }
        if (elected) { if (wg == 0) mbar_arrive_both(rY.empty(full0), rank ^ 1); mbar_arrive_both(rZ.empty(full0), rank ^ 1); }
      }
      {
        uint32_t v[16];
#pragma unroll
        for (int i = 0; i < 16; i++) { const float ri = (i & 1) ? rinv1 : rinv0; v[i] = pack_bf16(o[2 * i] * ri, o[2 * i + 1] * ri); }
#pragma unroll
        for (int i = 0; i < 32; i++) { const float ri = (i & 1) ? rinv1 : rinv0; pend[i] = pack_bf16(o[32 + 2 * i] * ri, o[33 + 2 * i] * ri); }
        stage_in(v);
      }
    }

    const unsigned otarget = ld_relaxed(&prm.epoch[cta]) + 1u, target = 3u * otarget;
    const uint32_t bhi = 0x40000040u | (rank ? 4u << 17 : 0u);
    float acc[80];
    {
      {
        const uint32_t da = descA0 + r.slot() * (SLOT_BYTES >> 4), db = descB0 + r.slot() * (SLOT_BYTES >> 4);
        mbar_wait(r.full(full0), r.phase());
        if (wg == 0) tok_wait(14); else if (wg == 2) tok_wait(15);
        wg_fence();
        wgmma_ss_n160_tb1_init(acc, desc(da), desc(db, 0, bhi));
#pragma unroll
        for (int k = 1; k < 4; k++) wgmma_ss_n160_tb1(acc, desc(da, k * 32), desc(db, k * 2048, bhi));
        wg_commit();
        if (wg == 0) tok_pass(15);
        send(1, 0);
        r.u++;
      }
#pragma unroll 1
      for (int ks = 1; ks < 24 - TAIL_L; ks++) {
        const uint32_t da = descA0 + r.slot() * (SLOT_BYTES >> 4), db = descB0 + r.slot() * (SLOT_BYTES >> 4);
        mbar_wait(r.full(full0), r.phase());
        wg_fence();
        wgmma_ss_n160_tb1(acc, desc(da), desc(db, 0, bhi));
        wg_commit();
        wg_wait<1>();
        if (elected) mbar_arrive_both(Ring{r.u - 1}.empty(full0), rank ^ 1);
#pragma unroll
        for (int k = 1; k < 4; k++) wgmma_ss_n160_tb1(acc, desc(da, k * 32), desc(db, k * 2048, bhi));
        wg_commit();
        {
          if (ks == FL2_B1)      { landed(3, Int<0>{}); stage_in(pend);      send(1, 1); }
          else if (ks == FL2_B2) { landed(4, Int<0>{}); stage_in(pend + 16); send(1, 2); }
          else if (ks == FL2_LD) { landed(5, Int<0>{}); }
        }
        r.u++;
      }
      static_assert(TAIL_L == NSLOT - 1, "the slots of the last NSLOT ring uses are not released");
      if (wg > 0) {
#pragma unroll
        for (int i = 0; i < TAIL_L; i++) mbar_wait((r + i).full(full0), (r + i).phase());
        tok_wait(3 + wg);
      } else {
        mbar_wait(r.full(full0), r.phase());
        mbar_wait((r + 1).full(full0), (r + 1).phase());
      }
      wg_fence();
#pragma unroll
      for (int i = 0; i < TAIL_L; i++) {
        const uint32_t da = descA0 + (r + i).slot() * (SLOT_BYTES >> 4), db = descB0 + (r + i).slot() * (SLOT_BYTES >> 4);
        if (i == TAIL_L - 1 && wg == 0) mbar_wait((r + i).full(full0), (r + i).phase());
#pragma unroll
        for (int k = 0; k < 4; k++) wgmma_ss_n160_tb1(acc, desc(da, k * 32), desc(db, k * 2048, bhi));
      }
      wg_commit();
      if (wg < 2) tok_pass(4 + wg);
      wg_wait<0>();
    }
    {
      const int lane = lane_id(), t = warp * 32 + lane;
#pragma unroll
      for (int q = 0; q < 4; q++) {
        const int blk0 = q == 0 ? 0 : q == 1 ? 6 : q == 2 ? 10 : 16, npk = (q & 1) ? 2 : 3;
        if (q != split) {
          const int dcta = (grp * 8 + 2 * q + (j8 & 1)) * 2 + rank;
          const int srcslot = split < q ? split : split - 1;
          uint4* dst = prm.part + (size_t)(dcta * 3 + srcslot) * (3 * 384) + t;
#pragma unroll
          for (int i = 0; i < 3; i++) {
            if (i < npk) {
              const int a = 4 * blk0 + 8 * i;
              __stcg(dst + i * 384, make_uint4(pack_bf16(acc[a], acc[a + 1]), pack_bf16(acc[a + 2], acc[a + 3]),
                                               pack_bf16(acc[a + 4], acc[a + 5]), pack_bf16(acc[a + 6], acc[a + 7])));
            }
          }
        }
      }
      __syncwarp();
      if (lane < 4 && lane != split) {
        const int dcta = (grp * 8 + 2 * lane + (j8 & 1)) * 2 + rank;
        red_release_add(&prm.xflag[dcta * 12 + warp], 1u);
      }
      const int nown = (split & 1) ? 2 : 3;
      float own[24];
#pragma unroll
      for (int i = 0; i < 24; i++)
        own[i] = split == 0 ? acc[i] : split == 1 ? acc[24 + (i & 15)] : split == 2 ? acc[40 + i] : acc[64 + (i & 15)];
      spin_until(&prm.xflag[cta * 12 + warp], target);
      {
        const uint4* src = prm.part + (size_t)(cta * 3) * (3 * 384) + t;
        uint4 v[9];
#pragma unroll
        for (int sidx = 0; sidx < 3; sidx++) {
          v[3 * sidx]     = __ldcg(src + (3 * sidx) * 384);
          v[3 * sidx + 1] = __ldcg(src + (3 * sidx + 1) * 384);
          v[3 * sidx + 2] = nown == 3 ? __ldcg(src + (3 * sidx + 2) * 384) : make_uint4(0u, 0u, 0u, 0u);
        }
#pragma unroll
        for (int sidx = 0; sidx < 3; sidx++) {
#pragma unroll
          for (int i = 0; i < 3; i++) {
            const uint32_t w[4] = {v[3 * sidx + i].x, v[3 * sidx + i].y, v[3 * sidx + i].z, v[3 * sidx + i].w};
#pragma unroll
            for (int k = 0; k < 4; k++) {
              own[8 * i + 2 * k]     += __uint_as_float(w[k] << 16);
              own[8 * i + 2 * k + 1] += __uint_as_float(w[k] & 0xffff0000u);
            }
          }
        }
      }
      stg_acquire();
      {
        const int r8 = lane & 7;
        const uint32_t st_base = wstg + (((lane >> 3) & 1) * 8 + r8) * 128;
#pragma unroll
        for (int jj = 0; jj < 3; jj++) {
          const uint32_t addr = st_base + (((2 * jj + (lane >> 4)) ^ r8) << 4);
          asm volatile("stmatrix.sync.aligned.m8n8.x4.shared.b16 [%0], {%1, %2, %3, %4};"
                       :: "r"(addr), "r"(pack_bf16(own[8 * jj], own[8 * jj + 1])), "r"(pack_bf16(own[8 * jj + 2], own[8 * jj + 3])),
                          "r"(pack_bf16(own[8 * jj + 4], own[8 * jj + 5])), "r"(pack_bf16(own[8 * jj + 6], own[8 * jj + 7])) : "memory");
        }
        __syncwarp();
        const int a0 = split == 0 ? 0 : split == 1 ? 48 : split == 2 ? 80 : 128;
        const int nch = 2 * nown;
        uint8_t* ob = reinterpret_cast<uint8_t*>(out) + ((size_t)(192 * bp + 16 * warp) * 1280 + 640 * prob + 320 * (j8 & 1)) * 2;
#pragma unroll
        for (int i = 0; i < 3; i++) {
          const int idx = i * 32 + lane;
          const int row = nown == 3 ? idx / 6 : idx >> 2, ch = idx - row * nch;
          if (row < 16) {
            uint4 w;
            asm volatile("ld.shared.v4.u32 {%0, %1, %2, %3}, [%4];" : "=r"(w.x), "=r"(w.y), "=r"(w.z), "=r"(w.w)
                         : "r"(wstg + row * 128 + ((ch ^ (row & 7)) << 4)) : "memory");
            const int a = a0 + 8 * ch;
            const int col = rank == 0 ? a : (a < 128 ? 192 + (a ^ 32) : 32 + a);
            *reinterpret_cast<uint4*>(ob + (size_t)row * 2560 + col * 2) = w;
          }
        }
      }
      if (t == 0) prm.epoch[cta] = otarget;
    }
  }
}

typedef CUresult (*EncodeFn)(CUtensorMap*, CUtensorMapDataType, cuuint32_t, void*, const cuuint64_t*, const cuuint64_t*,
                             const cuuint32_t*, const cuuint32_t*, CUtensorMapInterleave, CUtensorMapSwizzle,
                             CUtensorMapL2promotion, CUtensorMapFloatOOBfill);

void make_map(EncodeFn enc, CUtensorMap* m, const void* ptr, int rank, const uint64_t* dims, const uint64_t* strides,
              const uint32_t* box) {
  cuuint64_t d[3], s[2]; cuuint32_t b[3], e[3] = {1, 1, 1};
  for (int i = 0; i < rank; i++) { d[i] = dims[i]; b[i] = box[i]; }
  for (int i = 0; i + 1 < rank; i++) s[i] = strides[i];
  enc(m, CU_TENSOR_MAP_DATA_TYPE_BFLOAT16, rank, const_cast<void*>(ptr), d, s, b, e, CU_TENSOR_MAP_INTERLEAVE_NONE,
      CU_TENSOR_MAP_SWIZZLE_128B, CU_TENSOR_MAP_L2_PROMOTION_L2_128B, CU_TENSOR_MAP_FLOAT_OOB_FILL_NONE);
}

}

extern "C" void kernel_launch(void* const* d_in, const int* in_sizes, int n_in, void* d_out, int out_size) {
  (void)in_sizes; (void)n_in; (void)out_size;
  static EncodeFn enc = nullptr;
  static void *o_ptr = nullptr, *part_ptr = nullptr, *ready_ptr = nullptr, *xflag_ptr = nullptr, *epoch_ptr = nullptr;
  if (!enc) {
    void* fn = nullptr; cudaDriverEntryPointQueryResult st;
    cudaGetDriverEntryPoint("cuTensorMapEncodeTiled", &fn, cudaEnableDefault, &st);
    enc = (EncodeFn)fn;
    cudaGetSymbolAddress(&o_ptr, g_O);
    cudaGetSymbolAddress(&part_ptr, g_part);
    cudaGetSymbolAddress(&ready_ptr, g_ready);
    cudaGetSymbolAddress(&xflag_ptr, g_xflag);
    cudaGetSymbolAddress(&epoch_ptr, g_epoch);
    cudaFuncSetAttribute(fused_attn_kernel, cudaFuncAttributeMaxDynamicSharedMemorySize, SMEM_BYTES);
  }
  Params prm;
  for (int p = 0; p < 2; p++) {
    const void* x = d_in[5 * p + 0]; const void* k = d_in[5 * p + 1]; const void* v = d_in[5 * p + 2];
    const void* wq = d_in[5 * p + 3]; const void* wo = d_in[5 * p + 4];
    { uint64_t d[2] = {640, 768}, s[1] = {1280};              uint32_t b[2] = {64, 96};    make_map(enc, &prm.x[p],  x,  2, d, s, b); }
    { uint64_t d[2] = {640, 768}, s[1] = {1280};              uint32_t b[2] = {64, 192};   make_map(enc, &prm.x1[p], x,  2, d, s, b); }
    { uint64_t d[3] = {64, 640, 96}, s[2] = {12288, 128};     uint32_t b[3] = {64, 64, 3}; make_map(enc, &prm.wq[p], wq, 3, d, s, b); }
    { uint64_t d[3] = {64, 24576, 3}, s[2] = {384, 128};      uint32_t b[3] = {64, 96, 3}; make_map(enc, &prm.k[p],  k,  3, d, s, b); }
    { uint64_t d[3] = {64, 24576, 3}, s[2] = {384, 128};      uint32_t b[3] = {64, 96, 1}; make_map(enc, &prm.k1[p], k,  3, d, s, b); }
    { uint64_t d[3] = {64, 24576, 3}, s[2] = {384, 128};      uint32_t b[3] = {64, 96, 3}; make_map(enc, &prm.v[p],  v,  3, d, s, b); }
    { uint64_t d[3] = {64, 24576, 3}, s[2] = {384, 128};      uint32_t b[3] = {64, 96, 1}; make_map(enc, &prm.v1[p], v,  3, d, s, b); }
    prm.kptr[p] = (const uint8_t*)k; prm.vptr[p] = (const uint8_t*)v;
    prm.wqptr[p] = (const uint8_t*)wq;
    { uint64_t d[2] = {640, 6144}, s[1] = {1280};             uint32_t b[2] = {64, 64};    make_map(enc, &prm.wo[p], wo, 2, d, s, b); }
  }
  { uint64_t d[2] = {6144, 1536}, s[1] = {12288};        uint32_t b[2] = {64, 16};    make_map(enc, &prm.o_st, o_ptr, 2, d, s, b); }
  { uint64_t d[2] = {6144, 1536}, s[1] = {12288};        uint32_t b[2] = {64, 96};    make_map(enc, &prm.o_ld, o_ptr, 2, d, s, b); }
  prm.part = (uint4*)part_ptr; prm.ready = (unsigned*)ready_ptr; prm.xflag = (unsigned*)xflag_ptr; prm.epoch = (unsigned*)epoch_ptr;
  fused_attn_kernel<<<128, NTHREADS, SMEM_BYTES>>>(prm, (__nv_bfloat16*)d_out);
}
```

```cpp
#include <cuda_runtime.h>
#include <cuda_bf16.h>
#include <cuda.h>
#include <stdint.h>

namespace {

constexpr int FL_B1 = 2,  FL_B2 = 5,  FL_LD = 7;
constexpr int FL2_B1 = 2, FL2_B2 = 5, FL2_LD = 8;
constexpr int TAIL_L = 3;
constexpr int PF_WIN = 10;
constexpr int PF_R0 = 0, PF_R1 = 8, PF_R2 = 11, PF_R3 = 21;

constexpr int NTHREADS   = 512;
constexpr int NSLOT      = 4;
constexpr int SLOT_BYTES = 49152;
constexpr int B_OFF      = 24576;
constexpr int KV_BYTES   = 36864;
constexpr int STG_BYTES  = 12 * 2048;
constexpr int SMEM_BYTES = NSLOT * SLOT_BYTES + STG_BYTES + 1024  ;

struct Params {
  CUtensorMap x[2], x1[2], wq[2], k[2], k1[2], v[2], v1[2], wo[2];
  CUtensorMap o_st, o_ld, out_st;
  const uint8_t* kptr[2];
  const uint8_t* vptr[2];
  const uint8_t* wqptr[2];
  uint4*    part;
  unsigned* ready;
  unsigned* xflag;
  unsigned* epoch;
};

__host__ __device__ __forceinline__ int logical_cluster(int c) {
  const unsigned tab = 0xE6CA8421u;
  int v, bp;
  if (c < 4)       { v = 0; bp = c; }
  else if (c < 36) { const int t = c - 4;  v = (tab >> (4 * (t & 7))) & 15;          bp = t >> 3; }
  else             { const int t = c - 36; v = ((tab >> (4 * (1 + t % 7))) & 15) + 1; bp = t / 7; }
  return (v >> 3) * 32 + bp * 8 + (v & 7);
}

__device__ __nv_bfloat16 g_O[1536 * 6144];
__device__ uint4         g_part[128 * 3 * 3 * 384];
__device__ unsigned      g_ready[8 * 32];
__device__ unsigned      g_xflag[128 * 12];
__device__ unsigned      g_epoch[128];

__device__ __forceinline__ uint32_t smem_u32(const void* p) { return (uint32_t)__cvta_generic_to_shared(p); }
__device__ __forceinline__ void mbar_init(uint32_t bar, uint32_t count) {
  asm volatile("mbarrier.init.shared::cta.b64 [%0], %1;" :: "r"(bar), "r"(count) : "memory");
}
__device__ __forceinline__ void mbar_expect_tx(uint32_t bar, uint32_t bytes) {
  asm volatile("mbarrier.arrive.expect_tx.shared::cta.b64 _, [%0], %1;" :: "r"(bar), "r"(bytes) : "memory");
}
__device__ __forceinline__ void mbar_arrive_both(uint32_t bar, uint32_t peer) {
  asm volatile("{\n.reg .b32 r1;\n"
               "mapa.shared::cluster.u32 r1, %1, %2;\n"
               "mbarrier.arrive.shared::cta.b64 _, [%0];\n"
               "mbarrier.arrive.shared::cluster.b64 _, [r1];\n}"
               :: "r"(bar), "r"(bar + 8 * NSLOT), "r"(peer) : "memory");
}
__device__ __forceinline__ void mbar_wait(uint32_t bar, uint32_t parity) {
  asm volatile("{\n.reg .pred P1;\n.reg .u32 cnt;\nmov.u32 cnt, 0;\n"
               "LAB_WAIT:\n"
               "mbarrier.try_wait.parity.shared::cta.b64 P1, [%0], %1;\n"
               "@P1 bra DONE;\n"
               "add.u32 cnt, cnt, 1;\n"
               "setp.lt.u32 P1, cnt, 16777216;\n"
               "@P1 bra LAB_WAIT;\n"
               "trap;\n"
               "DONE:\n}"
               :: "r"(bar), "r"(parity) : "memory");
}
__device__ __forceinline__ uint64_t policy_evict_first() {
  uint64_t p; asm volatile("createpolicy.fractional.L2::evict_first.b64 %0, 1.0;" : "=l"(p)); return p;
}
__device__ __forceinline__ void tma_2d_nohint(uint32_t dst, const CUtensorMap* m, uint32_t bar, int c0, int c1) {
  asm volatile("cp.async.bulk.tensor.2d.shared::cluster.global.mbarrier::complete_tx::bytes [%0], [%1, {%3, %4}], [%2];"
               :: "r"(dst), "l"(m), "r"(bar), "r"(c0), "r"(c1) : "memory");
}
__device__ __forceinline__ void tma_2d_mc(uint32_t dst, const CUtensorMap* m, uint32_t bar, int c0, int c1) {
  asm volatile("cp.async.bulk.tensor.2d.shared::cluster.global.mbarrier::complete_tx::bytes.multicast::cluster [%0], [%1, {%3, %4}], [%2], %5;"
               :: "r"(dst), "l"(m), "r"(bar), "r"(c0), "r"(c1), "h"((uint16_t)3) : "memory");
}
__device__ __forceinline__ void tma_2d(uint32_t dst, const CUtensorMap* m, uint32_t bar, int c0, int c1, uint64_t pol) {
  asm volatile("cp.async.bulk.tensor.2d.shared::cluster.global.mbarrier::complete_tx::bytes.L2::cache_hint [%0], [%1, {%3, %4}], [%2], %5;"
               :: "r"(dst), "l"(m), "r"(bar), "r"(c0), "r"(c1), "l"(pol) : "memory");
}
__device__ __forceinline__ void tma_3d(uint32_t dst, const CUtensorMap* m, uint32_t bar, int c0, int c1, int c2, uint64_t pol) {
  asm volatile("cp.async.bulk.tensor.3d.shared::cluster.global.mbarrier::complete_tx::bytes.L2::cache_hint [%0], [%1, {%3, %4, %5}], [%2], %6;"
               :: "r"(dst), "l"(m), "r"(bar), "r"(c0), "r"(c1), "r"(c2), "l"(pol) : "memory");
}
__device__ __forceinline__ void tma_store_2d(const CUtensorMap* m, uint32_t src, int c0, int c1) {
  asm volatile("cp.async.bulk.tensor.2d.global.shared::cta.bulk_group [%0, {%2, %3}], [%1];"
               :: "l"(m), "r"(src), "r"(c0), "r"(c1) : "memory");
}
__device__ __forceinline__ bool mbar_test(uint32_t bar, uint32_t parity) {
  uint32_t ok;
  asm volatile("{\n.reg .pred p;\nmbarrier.test_wait.parity.shared::cta.b64 p, [%1], %2;\nselp.u32 %0, 1, 0, p;\n}"
               : "=r"(ok) : "r"(bar), "r"(parity) : "memory");
  return ok;
}
__device__ __forceinline__ int lane_id() { int l; asm volatile("mov.u32 %0, %%laneid;" : "=r"(l)); return l; }
__device__ __forceinline__ void mbar_arrive(uint32_t bar) {
  asm volatile("mbarrier.arrive.shared::cta.b64 _, [%0];" :: "r"(bar) : "memory");
}
__device__ __forceinline__ void wg_fence()  { asm volatile("wgmma.fence.sync.aligned;" ::: "memory"); }
__device__ __forceinline__ void wg_commit() { asm volatile("wgmma.commit_group.sync.aligned;" ::: "memory"); }
template <int N> __device__ __forceinline__ void wg_wait() { asm volatile("wgmma.wait_group.sync.aligned %0;" :: "n"(N) : "memory"); }
__device__ __forceinline__ void tok_wait(int id) { asm volatile("bar.sync %0, 256;" :: "r"(id) : "memory"); }
__device__ __forceinline__ void tok_pass(int id) { asm volatile("bar.arrive %0, 256;" :: "r"(id) : "memory"); }
__device__ __forceinline__ void cluster_arrive_relaxed() { asm volatile("barrier.cluster.arrive.relaxed.aligned;" ::: "memory"); }
__device__ __forceinline__ void cluster_wait()           { asm volatile("barrier.cluster.wait.aligned;" ::: "memory"); }
__device__ __forceinline__ unsigned ld_relaxed(const unsigned* p) {
  unsigned v; asm volatile("ld.relaxed.gpu.global.u32 %0, [%1];" : "=r"(v) : "l"(p) : "memory"); return v;
}
__device__ __forceinline__ unsigned ld_acquire(const unsigned* p) {
  unsigned v; asm volatile("ld.acquire.gpu.global.u32 %0, [%1];" : "=r"(v) : "l"(p) : "memory"); return v;
}
__device__ __forceinline__ void spin_until(const unsigned* p, unsigned target) {
  asm volatile("{\n.reg .pred P1;\n.reg .u32 cnt, v;\nmov.u32 cnt, 0;\n"
               "LAB_SPIN:\n"
               "ld.acquire.gpu.global.u32 v, [%0];\n"
               "sub.u32 v, v, %1;\n"
               "setp.ge.s32 P1, v, 0;\n"
               "@P1 bra DONE;\n"
               "nanosleep.u32 20;\n"
               "add.u32 cnt, cnt, 1;\n"
               "setp.lt.u32 P1, cnt, 4194304;\n"
               "@P1 bra LAB_SPIN;\n"
               "trap;\n"
               "DONE:\n}"
               :: "l"(p), "r"(target) : "memory");
}
__device__ __forceinline__ uint32_t desc_lo(uint32_t addr, uint32_t lbo) { return ((addr & 0x3FFFF) >> 4) | ((lbo >> 4) << 16); }
__device__ __forceinline__ uint64_t desc(uint32_t lo, uint32_t byte_off = 0, uint32_t hi = 0x40000040u) {
  uint64_t d;
  asm("mov.b64 %0, {%1, %2};" : "=l"(d) : "r"(lo + (byte_off >> 4)), "r"(hi));
  return d;
}
__device__ __forceinline__ uint32_t pack_bf16(float lo, float hi) {
  uint32_t r; asm("cvt.rn.bf16x2.f32 %0, %1, %2;" : "=r"(r) : "f"(hi), "f"(lo)); return r;
}
__device__ __forceinline__ float ex2(float x) { float r; asm("ex2.approx.ftz.f32 %0, %1;" : "=f"(r) : "f"(x)); return r; }

__device__ __forceinline__ void wgmma_ss_n192_tb1(float (&d)[96], uint64_t descA, uint64_t descB) {
  asm volatile("{\n.reg .pred p;\n"
    "setp.ne.b32 p, 1, 0;\n"
    "wgmma.mma_async.sync.aligned.m64n192k16.f32.bf16.bf16 "
    "{%0, %1, %2, %3, %4, %5, %6, %7, %8, %9, %10, %11, %12, %13, %14, %15, "
    "%16, %17, %18, %19, %20, %21, %22, %23, %24, %25, %26, %27, %28, %29, %30, %31, "
    "%32, %33, %34, %35, %36, %37, %38, %39, %40, %41, %42, %43, %44, %45, %46, %47, "
    "%48, %49, %50, %51, %52, %53, %54, %55, %56, %57, %58, %59, %60, %61, %62, %63, "
    "%64, %65, %66, %67, %68, %69, %70, %71, %72, %73, %74, %75, %76, %77, %78, %79, "
    "%80, %81, %82, %83, %84, %85, %86, %87, %88, %89, %90, %91, %92, %93, %94, %95}, "
    "%96, %97, p, 1, 1, 0, 1;\n}\n"
    : "+f"(d[0]), "+f"(d[1]), "+f"(d[2]), "+f"(d[3]), "+f"(d[4]), "+f"(d[5]), "+f"(d[6]), "+f"(d[7]),
      "+f"(d[8]), "+f"(d[9]), "+f"(d[10]), "+f"(d[11]), "+f"(d[12]), "+f"(d[13]), "+f"(d[14]), "+f"(d[15]),
      "+f"(d[16]), "+f"(d[17]), "+f"(d[18]), "+f"(d[19]), "+f"(d[20]), "+f"(d[21]), "+f"(d[22]), "+f"(d[23]),
      "+f"(d[24]), "+f"(d[25]), "+f"(d[26]), "+f"(d[27]), "+f"(d[28]), "+f"(d[29]), "+f"(d[30]), "+f"(d[31]),
      "+f"(d[32]), "+f"(d[33]), "+f"(d[34]), "+f"(d[35]), "+f"(d[36]), "+f"(d[37]), "+f"(d[38]), "+f"(d[39]),
      "+f"(d[40]), "+f"(d[41]), "+f"(d[42]), "+f"(d[43]), "+f"(d[44]), "+f"(d[45]), "+f"(d[46]), "+f"(d[47]),
      "+f"(d[48]), "+f"(d[49]), "+f"(d[50]), "+f"(d[51]), "+f"(d[52]), "+f"(d[53]), "+f"(d[54]), "+f"(d[55]),
      "+f"(d[56]), "+f"(d[57]), "+f"(d[58]), "+f"(d[59]), "+f"(d[60]), "+f"(d[61]), "+f"(d[62]), "+f"(d[63]),
      "+f"(d[64]), "+f"(d[65]), "+f"(d[66]), "+f"(d[67]), "+f"(d[68]), "+f"(d[69]), "+f"(d[70]), "+f"(d[71]),
      "+f"(d[72]), "+f"(d[73]), "+f"(d[74]), "+f"(d[75]), "+f"(d[76]), "+f"(d[77]), "+f"(d[78]), "+f"(d[79]),
      "+f"(d[80]), "+f"(d[81]), "+f"(d[82]), "+f"(d[83]), "+f"(d[84]), "+f"(d[85]), "+f"(d[86]), "+f"(d[87]),
      "+f"(d[88]), "+f"(d[89]), "+f"(d[90]), "+f"(d[91]), "+f"(d[92]), "+f"(d[93]), "+f"(d[94]), "+f"(d[95])
    : "l"(descA), "l"(descB));
}

__device__ __forceinline__ void wgmma_ss_n192_tb1_init(float (&d)[96], uint64_t descA, uint64_t descB) {
  asm volatile("{\n.reg .pred p;\n"
    "setp.ne.b32 p, 0, 0;\n"
    "wgmma.mma_async.sync.aligned.m64n192k16.f32.bf16.bf16 "
    "{%0, %1, %2, %3, %4, %5, %6, %7, %8, %9, %10, %11, %12, %13, %14, %15, "
    "%16, %17, %18, %19, %20, %21, %22, %23, %24, %25, %26, %27, %28, %29, %30, %31, "
    "%32, %33, %34, %35, %36, %37, %38, %39, %40, %41, %42, %43, %44, %45, %46, %47, "
    "%48, %49, %50, %51, %52, %53, %54, %55, %56, %57, %58, %59, %60, %61, %62, %63, "
    "%64, %65, %66, %67, %68, %69, %70, %71, %72, %73, %74, %75, %76, %77, %78, %79, "
    "%80, %81, %82, %83, %84, %85, %86, %87, %88, %89, %90, %91, %92, %93, %94, %95}, "
    "%96, %97, p, 1, 1, 0, 1;\n}\n"
    : "=f"(d[0]), "=f"(d[1]), "=f"(d[2]), "=f"(d[3]), "=f"(d[4]), "=f"(d[5]), "=f"(d[6]), "=f"(d[7]),
      "=f"(d[8]), "=f"(d[9]), "=f"(d[10]), "=f"(d[11]), "=f"(d[12]), "=f"(d[13]), "=f"(d[14]), "=f"(d[15]),
      "=f"(d[16]), "=f"(d[17]), "=f"(d[18]), "=f"(d[19]), "=f"(d[20]), "=f"(d[21]), "=f"(d[22]), "=f"(d[23]),
      "=f"(d[24]), "=f"(d[25]), "=f"(d[26]), "=f"(d[27]), "=f"(d[28]), "=f"(d[29]), "=f"(d[30]), "=f"(d[31]),
      "=f"(d[32]), "=f"(d[33]), "=f"(d[34]), "=f"(d[35]), "=f"(d[36]), "=f"(d[37]), "=f"(d[38]), "=f"(d[39]),
      "=f"(d[40]), "=f"(d[41]), "=f"(d[42]), "=f"(d[43]), "=f"(d[44]), "=f"(d[45]), "=f"(d[46]), "=f"(d[47]),
      "=f"(d[48]), "=f"(d[49]), "=f"(d[50]), "=f"(d[51]), "=f"(d[52]), "=f"(d[53]), "=f"(d[54]), "=f"(d[55]),
      "=f"(d[56]), "=f"(d[57]), "=f"(d[58]), "=f"(d[59]), "=f"(d[60]), "=f"(d[61]), "=f"(d[62]), "=f"(d[63]),
      "=f"(d[64]), "=f"(d[65]), "=f"(d[66]), "=f"(d[67]), "=f"(d[68]), "=f"(d[69]), "=f"(d[70]), "=f"(d[71]),
      "=f"(d[72]), "=f"(d[73]), "=f"(d[74]), "=f"(d[75]), "=f"(d[76]), "=f"(d[77]), "=f"(d[78]), "=f"(d[79]),
      "=f"(d[80]), "=f"(d[81]), "=f"(d[82]), "=f"(d[83]), "=f"(d[84]), "=f"(d[85]), "=f"(d[86]), "=f"(d[87]),
      "=f"(d[88]), "=f"(d[89]), "=f"(d[90]), "=f"(d[91]), "=f"(d[92]), "=f"(d[93]), "=f"(d[94]), "=f"(d[95])
    : "l"(descA), "l"(descB));
}

__device__ __forceinline__ void wgmma_ss_n160_tb1(float (&d)[80], uint64_t descA, uint64_t descB) {
  asm volatile("{\n.reg .pred p;\n"
    "setp.ne.b32 p, 1, 0;\n"
    "wgmma.mma_async.sync.aligned.m64n160k16.f32.bf16.bf16 "
    "{%0, %1, %2, %3, %4, %5, %6, %7, %8, %9, %10, %11, %12, %13, %14, %15, "
    "%16, %17, %18, %19, %20, %21, %22, %23, %24, %25, %26, %27, %28, %29, %30, %31, "
    "%32, %33, %34, %35, %36, %37, %38, %39, %40, %41, %42, %43, %44, %45, %46, %47, "
    "%48, %49, %50, %51, %52, %53, %54, %55, %56, %57, %58, %59, %60, %61, %62, %63, "
    "%64, %65, %66, %67, %68, %69, %70, %71, %72, %73, %74, %75, %76, %77, %78, %79}, "
    "%80, %81, p, 1, 1, 0, 1;\n}\n"
    : "+f"(d[0]), "+f"(d[1]), "+f"(d[2]), "+f"(d[3]), "+f"(d[4]), "+f"(d[5]), "+f"(d[6]), "+f"(d[7]),
      "+f"(d[8]), "+f"(d[9]), "+f"(d[10]), "+f"(d[11]), "+f"(d[12]), "+f"(d[13]), "+f"(d[14]), "+f"(d[15]),
      "+f"(d[16]), "+f"(d[17]), "+f"(d[18]), "+f"(d[19]), "+f"(d[20]), "+f"(d[21]), "+f"(d[22]), "+f"(d[23]),
      "+f"(d[24]), "+f"(d[25]), "+f"(d[26]), "+f"(d[27]), "+f"(d[28]), "+f"(d[29]), "+f"(d[30]), "+f"(d[31]),
      "+f"(d[32]), "+f"(d[33]), "+f"(d[34]), "+f"(d[35]), "+f"(d[36]), "+f"(d[37]), "+f"(d[38]), "+f"(d[39]),
      "+f"(d[40]), "+f"(d[41]), "+f"(d[42]), "+f"(d[43]), "+f"(d[44]), "+f"(d[45]), "+f"(d[46]), "+f"(d[47]),
      "+f"(d[48]), "+f"(d[49]), "+f"(d[50]), "+f"(d[51]), "+f"(d[52]), "+f"(d[53]), "+f"(d[54]), "+f"(d[55]),
      "+f"(d[56]), "+f"(d[57]), "+f"(d[58]), "+f"(d[59]), "+f"(d[60]), "+f"(d[61]), "+f"(d[62]), "+f"(d[63]),
      "+f"(d[64]), "+f"(d[65]), "+f"(d[66]), "+f"(d[67]), "+f"(d[68]), "+f"(d[69]), "+f"(d[70]), "+f"(d[71]),
      "+f"(d[72]), "+f"(d[73]), "+f"(d[74]), "+f"(d[75]), "+f"(d[76]), "+f"(d[77]), "+f"(d[78]), "+f"(d[79])
    : "l"(descA), "l"(descB));
}

__device__ __forceinline__ void wgmma_ss_n160_tb1_init(float (&d)[80], uint64_t descA, uint64_t descB) {
  asm volatile("{\n.reg .pred p;\n"
    "setp.ne.b32 p, 0, 0;\n"
    "wgmma.mma_async.sync.aligned.m64n160k16.f32.bf16.bf16 "
    "{%0, %1, %2, %3, %4, %5, %6, %7, %8, %9, %10, %11, %12, %13, %14, %15, "
    "%16, %17, %18, %19, %20, %21, %22, %23, %24, %25, %26, %27, %28, %29, %30, %31, "
    "%32, %33, %34, %35, %36, %37, %38, %39, %40, %41, %42, %43, %44, %45, %46, %47, "
    "%48, %49, %50, %51, %52, %53, %54, %55, %56, %57, %58, %59, %60, %61, %62, %63, "
    "%64, %65, %66, %67, %68, %69, %70, %71, %72, %73, %74, %75, %76, %77, %78, %79}, "
    "%80, %81, p, 1, 1, 0, 1;\n}\n"
    : "=f"(d[0]), "=f"(d[1]), "=f"(d[2]), "=f"(d[3]), "=f"(d[4]), "=f"(d[5]), "=f"(d[6]), "=f"(d[7]),
      "=f"(d[8]), "=f"(d[9]), "=f"(d[10]), "=f"(d[11]), "=f"(d[12]), "=f"(d[13]), "=f"(d[14]), "=f"(d[15]),
      "=f"(d[16]), "=f"(d[17]), "=f"(d[18]), "=f"(d[19]), "=f"(d[20]), "=f"(d[21]), "=f"(d[22]), "=f"(d[23]),
      "=f"(d[24]), "=f"(d[25]), "=f"(d[26]), "=f"(d[27]), "=f"(d[28]), "=f"(d[29]), "=f"(d[30]), "=f"(d[31]),
      "=f"(d[32]), "=f"(d[33]), "=f"(d[34]), "=f"(d[35]), "=f"(d[36]), "=f"(d[37]), "=f"(d[38]), "=f"(d[39]),
      "=f"(d[40]), "=f"(d[41]), "=f"(d[42]), "=f"(d[43]), "=f"(d[44]), "=f"(d[45]), "=f"(d[46]), "=f"(d[47]),
      "=f"(d[48]), "=f"(d[49]), "=f"(d[50]), "=f"(d[51]), "=f"(d[52]), "=f"(d[53]), "=f"(d[54]), "=f"(d[55]),
      "=f"(d[56]), "=f"(d[57]), "=f"(d[58]), "=f"(d[59]), "=f"(d[60]), "=f"(d[61]), "=f"(d[62]), "=f"(d[63]),
      "=f"(d[64]), "=f"(d[65]), "=f"(d[66]), "=f"(d[67]), "=f"(d[68]), "=f"(d[69]), "=f"(d[70]), "=f"(d[71]),
      "=f"(d[72]), "=f"(d[73]), "=f"(d[74]), "=f"(d[75]), "=f"(d[76]), "=f"(d[77]), "=f"(d[78]), "=f"(d[79])
    : "l"(descA), "l"(descB));
}

__device__ __forceinline__ void wgmma_rs_n96_tb0(float (&d)[48], uint32_t a0, uint32_t a1, uint32_t a2, uint32_t a3, uint64_t descB) {
  asm volatile("{\n.reg .pred p;\n"
    "setp.ne.b32 p, 1, 0;\n"
    "wgmma.mma_async.sync.aligned.m64n96k16.f32.bf16.bf16 "
    "{%0, %1, %2, %3, %4, %5, %6, %7, %8, %9, %10, %11, %12, %13, %14, %15, "
    "%16, %17, %18, %19, %20, %21, %22, %23, %24, %25, %26, %27, %28, %29, %30, %31, "
    "%32, %33, %34, %35, %36, %37, %38, %39, %40, %41, %42, %43, %44, %45, %46, %47}, "
    "{%48, %49, %50, %51}, %52, p, 1, 1, 0;\n}\n"
    : "+f"(d[0]), "+f"(d[1]), "+f"(d[2]), "+f"(d[3]), "+f"(d[4]), "+f"(d[5]), "+f"(d[6]), "+f"(d[7]),
      "+f"(d[8]), "+f"(d[9]), "+f"(d[10]), "+f"(d[11]), "+f"(d[12]), "+f"(d[13]), "+f"(d[14]), "+f"(d[15]),
      "+f"(d[16]), "+f"(d[17]), "+f"(d[18]), "+f"(d[19]), "+f"(d[20]), "+f"(d[21]), "+f"(d[22]), "+f"(d[23]),
      "+f"(d[24]), "+f"(d[25]), "+f"(d[26]), "+f"(d[27]), "+f"(d[28]), "+f"(d[29]), "+f"(d[30]), "+f"(d[31]),
      "+f"(d[32]), "+f"(d[33]), "+f"(d[34]), "+f"(d[35]), "+f"(d[36]), "+f"(d[37]), "+f"(d[38]), "+f"(d[39]),
      "+f"(d[40]), "+f"(d[41]), "+f"(d[42]), "+f"(d[43]), "+f"(d[44]), "+f"(d[45]), "+f"(d[46]), "+f"(d[47])
    : "r"(a0), "r"(a1), "r"(a2), "r"(a3), "l"(descB));
}

__device__ __forceinline__ void wgmma_rs_n96_tb0_init(float (&d)[48], uint32_t a0, uint32_t a1, uint32_t a2, uint32_t a3, uint64_t descB) {
  asm volatile("{\n.reg .pred p;\n"
    "setp.ne.b32 p, 0, 0;\n"
    "wgmma.mma_async.sync.aligned.m64n96k16.f32.bf16.bf16 "
    "{%0, %1, %2, %3, %4, %5, %6, %7, %8, %9, %10, %11, %12, %13, %14, %15, "
    "%16, %17, %18, %19, %20, %21, %22, %23, %24, %25, %26, %27, %28, %29, %30, %31, "
    "%32, %33, %34, %35, %36, %37, %38, %39, %40, %41, %42, %43, %44, %45, %46, %47}, "
    "{%48, %49, %50, %51}, %52, p, 1, 1, 0;\n}\n"
    : "=f"(d[0]), "=f"(d[1]), "=f"(d[2]), "=f"(d[3]), "=f"(d[4]), "=f"(d[5]), "=f"(d[6]), "=f"(d[7]),
      "=f"(d[8]), "=f"(d[9]), "=f"(d[10]), "=f"(d[11]), "=f"(d[12]), "=f"(d[13]), "=f"(d[14]), "=f"(d[15]),
      "=f"(d[16]), "=f"(d[17]), "=f"(d[18]), "=f"(d[19]), "=f"(d[20]), "=f"(d[21]), "=f"(d[22]), "=f"(d[23]),
      "=f"(d[24]), "=f"(d[25]), "=f"(d[26]), "=f"(d[27]), "=f"(d[28]), "=f"(d[29]), "=f"(d[30]), "=f"(d[31]),
      "=f"(d[32]), "=f"(d[33]), "=f"(d[34]), "=f"(d[35]), "=f"(d[36]), "=f"(d[37]), "=f"(d[38]), "=f"(d[39]),
      "=f"(d[40]), "=f"(d[41]), "=f"(d[42]), "=f"(d[43]), "=f"(d[44]), "=f"(d[45]), "=f"(d[46]), "=f"(d[47])
    : "r"(a0), "r"(a1), "r"(a2), "r"(a3), "l"(descB));
}

__device__ __forceinline__ void wgmma_rs_n128_tb1(float (&d)[64], uint32_t a0, uint32_t a1, uint32_t a2, uint32_t a3, uint64_t descB) {
  asm volatile("{\n.reg .pred p;\n"
    "setp.ne.b32 p, 1, 0;\n"
    "wgmma.mma_async.sync.aligned.m64n128k16.f32.bf16.bf16 "
    "{%0, %1, %2, %3, %4, %5, %6, %7, %8, %9, %10, %11, %12, %13, %14, %15, "
    "%16, %17, %18, %19, %20, %21, %22, %23, %24, %25, %26, %27, %28, %29, %30, %31, "
    "%32, %33, %34, %35, %36, %37, %38, %39, %40, %41, %42, %43, %44, %45, %46, %47, "
    "%48, %49, %50, %51, %52, %53, %54, %55, %56, %57, %58, %59, %60, %61, %62, %63}, "
    "{%64, %65, %66, %67}, %68, p, 1, 1, 1;\n}\n"
    : "+f"(d[0]), "+f"(d[1]), "+f"(d[2]), "+f"(d[3]), "+f"(d[4]), "+f"(d[5]), "+f"(d[6]), "+f"(d[7]),
      "+f"(d[8]), "+f"(d[9]), "+f"(d[10]), "+f"(d[11]), "+f"(d[12]), "+f"(d[13]), "+f"(d[14]), "+f"(d[15]),
      "+f"(d[16]), "+f"(d[17]), "+f"(d[18]), "+f"(d[19]), "+f"(d[20]), "+f"(d[21]), "+f"(d[22]), "+f"(d[23]),
      "+f"(d[24]), "+f"(d[25]), "+f"(d[26]), "+f"(d[27]), "+f"(d[28]), "+f"(d[29]), "+f"(d[30]), "+f"(d[31]),
      "+f"(d[32]), "+f"(d[33]), "+f"(d[34]), "+f"(d[35]), "+f"(d[36]), "+f"(d[37]), "+f"(d[38]), "+f"(d[39]),
      "+f"(d[40]), "+f"(d[41]), "+f"(d[42]), "+f"(d[43]), "+f"(d[44]), "+f"(d[45]), "+f"(d[46]), "+f"(d[47]),
      "+f"(d[48]), "+f"(d[49]), "+f"(d[50]), "+f"(d[51]), "+f"(d[52]), "+f"(d[53]), "+f"(d[54]), "+f"(d[55]),
      "+f"(d[56]), "+f"(d[57]), "+f"(d[58]), "+f"(d[59]), "+f"(d[60]), "+f"(d[61]), "+f"(d[62]), "+f"(d[63])
    : "r"(a0), "r"(a1), "r"(a2), "r"(a3), "l"(descB));
}

__device__ __forceinline__ void wgmma_rs_n128_tb1_init(float (&d)[64], uint32_t a0, uint32_t a1, uint32_t a2, uint32_t a3, uint64_t descB) {
  asm volatile("{\n.reg .pred p;\n"
    "setp.ne.b32 p, 0, 0;\n"
    "wgmma.mma_async.sync.aligned.m64n128k16.f32.bf16.bf16 "
    "{%0, %1, %2, %3, %4, %5, %6, %7, %8, %9, %10, %11, %12, %13, %14, %15, "
    "%16, %17, %18, %19, %20, %21, %22, %23, %24, %25, %26, %27, %28, %29, %30, %31, "
    "%32, %33, %34, %35, %36, %37, %38, %39, %40, %41, %42, %43, %44, %45, %46, %47, "
    "%48, %49, %50, %51, %52, %53, %54, %55, %56, %57, %58, %59, %60, %61, %62, %63}, "
    "{%64, %65, %66, %67}, %68, p, 1, 1, 1;\n}\n"
    : "=f"(d[0]), "=f"(d[1]), "=f"(d[2]), "=f"(d[3]), "=f"(d[4]), "=f"(d[5]), "=f"(d[6]), "=f"(d[7]),
      "=f"(d[8]), "=f"(d[9]), "=f"(d[10]), "=f"(d[11]), "=f"(d[12]), "=f"(d[13]), "=f"(d[14]), "=f"(d[15]),
      "=f"(d[16]), "=f"(d[17]), "=f"(d[18]), "=f"(d[19]), "=f"(d[20]), "=f"(d[21]), "=f"(d[22]), "=f"(d[23]),
      "=f"(d[24]), "=f"(d[25]), "=f"(d[26]), "=f"(d[27]), "=f"(d[28]), "=f"(d[29]), "=f"(d[30]), "=f"(d[31]),
      "=f"(d[32]), "=f"(d[33]), "=f"(d[34]), "=f"(d[35]), "=f"(d[36]), "=f"(d[37]), "=f"(d[38]), "=f"(d[39]),
      "=f"(d[40]), "=f"(d[41]), "=f"(d[42]), "=f"(d[43]), "=f"(d[44]), "=f"(d[45]), "=f"(d[46]), "=f"(d[47]),
      "=f"(d[48]), "=f"(d[49]), "=f"(d[50]), "=f"(d[51]), "=f"(d[52]), "=f"(d[53]), "=f"(d[54]), "=f"(d[55]),
      "=f"(d[56]), "=f"(d[57]), "=f"(d[58]), "=f"(d[59]), "=f"(d[60]), "=f"(d[61]), "=f"(d[62]), "=f"(d[63])
    : "r"(a0), "r"(a1), "r"(a2), "r"(a3), "l"(descB));
}

__device__ __forceinline__ void wgmma_rs_n64_tb1(float (&d)[32], uint32_t a0, uint32_t a1, uint32_t a2, uint32_t a3, uint64_t descB) {
  asm volatile("{\n.reg .pred p;\n"
    "setp.ne.b32 p, 1, 0;\n"
    "wgmma.mma_async.sync.aligned.m64n64k16.f32.bf16.bf16 "
    "{%0, %1, %2, %3, %4, %5, %6, %7, %8, %9, %10, %11, %12, %13, %14, %15, "
    "%16, %17, %18, %19, %20, %21, %22, %23, %24, %25, %26, %27, %28, %29, %30, %31}, "
    "{%32, %33, %34, %35}, %36, p, 1, 1, 1;\n}\n"
    : "+f"(d[0]), "+f"(d[1]), "+f"(d[2]), "+f"(d[3]), "+f"(d[4]), "+f"(d[5]), "+f"(d[6]), "+f"(d[7]),
      "+f"(d[8]), "+f"(d[9]), "+f"(d[10]), "+f"(d[11]), "+f"(d[12]), "+f"(d[13]), "+f"(d[14]), "+f"(d[15]),
      "+f"(d[16]), "+f"(d[17]), "+f"(d[18]), "+f"(d[19]), "+f"(d[20]), "+f"(d[21]), "+f"(d[22]), "+f"(d[23]),
      "+f"(d[24]), "+f"(d[25]), "+f"(d[26]), "+f"(d[27]), "+f"(d[28]), "+f"(d[29]), "+f"(d[30]), "+f"(d[31])
    : "r"(a0), "r"(a1), "r"(a2), "r"(a3), "l"(descB));
}

__device__ __forceinline__ void wgmma_rs_n64_tb1_init(float (&d)[32], uint32_t a0, uint32_t a1, uint32_t a2, uint32_t a3, uint64_t descB) {
  asm volatile("{\n.reg .pred p;\n"
    "setp.ne.b32 p, 0, 0;\n"
    "wgmma.mma_async.sync.aligned.m64n64k16.f32.bf16.bf16 "
    "{%0, %1, %2, %3, %4, %5, %6, %7, %8, %9, %10, %11, %12, %13, %14, %15, "
    "%16, %17, %18, %19, %20, %21, %22, %23, %24, %25, %26, %27, %28, %29, %30, %31}, "
    "{%32, %33, %34, %35}, %36, p, 1, 1, 1;\n}\n"
    : "=f"(d[0]), "=f"(d[1]), "=f"(d[2]), "=f"(d[3]), "=f"(d[4]), "=f"(d[5]), "=f"(d[6]), "=f"(d[7]),
      "=f"(d[8]), "=f"(d[9]), "=f"(d[10]), "=f"(d[11]), "=f"(d[12]), "=f"(d[13]), "=f"(d[14]), "=f"(d[15]),
      "=f"(d[16]), "=f"(d[17]), "=f"(d[18]), "=f"(d[19]), "=f"(d[20]), "=f"(d[21]), "=f"(d[22]), "=f"(d[23]),
      "=f"(d[24]), "=f"(d[25]), "=f"(d[26]), "=f"(d[27]), "=f"(d[28]), "=f"(d[29]), "=f"(d[30]), "=f"(d[31])
    : "r"(a0), "r"(a1), "r"(a2), "r"(a3), "l"(descB));
}

template <int V> struct Int { static constexpr int value = V; };

struct Ring {
  uint32_t u;
  __device__ __forceinline__ uint32_t slot()  const { return u & (NSLOT - 1); }
  __device__ __forceinline__ uint32_t phase() const { return (u >> 2) & 1; }
  __device__ __forceinline__ uint32_t full(uint32_t full0)   const { return full0 + 8 * slot(); }
  __device__ __forceinline__ uint32_t empty(uint32_t full0)  const { return full0 + 8 * NSLOT + 8 * slot(); }
  __device__ __forceinline__ uint32_t addr(uint32_t ring)    const { return ring + slot() * SLOT_BYTES; }
  __device__ __forceinline__ Ring operator+(uint32_t d) const { return Ring{u + d}; }
};

__device__ __forceinline__ void softmax96(float (&s)[48], uint32_t (&p)[24], float& r0, float& r1) {
  const float c = 0.07216878364870322f * 1.4426950408889634f;
  float a0[6], a1[6];
#pragma unroll
  for (int j = 0; j < 6; j++) {
    a0[j] = fmaxf(fmaxf(s[8 * j], s[8 * j + 1]), fmaxf(s[8 * j + 4], s[8 * j + 5]));
    a1[j] = fmaxf(fmaxf(s[8 * j + 2], s[8 * j + 3]), fmaxf(s[8 * j + 6], s[8 * j + 7]));
  }
  float m0 = fmaxf(fmaxf(fmaxf(a0[0], a0[1]), fmaxf(a0[2], a0[3])), fmaxf(a0[4], a0[5]));
  float m1 = fmaxf(fmaxf(fmaxf(a1[0], a1[1]), fmaxf(a1[2], a1[3])), fmaxf(a1[4], a1[5]));
  m0 = fmaxf(m0, __shfl_xor_sync(0xffffffffu, m0, 1));
  m1 = fmaxf(m1, __shfl_xor_sync(0xffffffffu, m1, 1));
  m0 = fmaxf(m0, __shfl_xor_sync(0xffffffffu, m0, 2));
  m1 = fmaxf(m1, __shfl_xor_sync(0xffffffffu, m1, 2));
  const float b0 = -m0 * c, b1 = -m1 * c;
  float l0 = 0.f, l1 = 0.f;
#pragma unroll
  for (int j = 0; j < 12; j++) {
    const float e0 = ex2(fmaf(s[4 * j],     c, b0)), e1 = ex2(fmaf(s[4 * j + 1], c, b0));
    const float e2 = ex2(fmaf(s[4 * j + 2], c, b1)), e3 = ex2(fmaf(s[4 * j + 3], c, b1));
    l0 += e0 + e1;
    l1 += e2 + e3;
    p[2 * j]     = pack_bf16(e0, e1);
    p[2 * j + 1] = pack_bf16(e2, e3);
  }
  l0 += __shfl_xor_sync(0xffffffffu, l0, 1);
  l1 += __shfl_xor_sync(0xffffffffu, l1, 1);
  l0 += __shfl_xor_sync(0xffffffffu, l0, 2);
  l1 += __shfl_xor_sync(0xffffffffu, l1, 2);
  asm("rcp.approx.ftz.f32 %0, %1;" : "=f"(r0) : "f"(l0));
  asm("rcp.approx.ftz.f32 %0, %1;" : "=f"(r1) : "f"(l1));
}

template <bool INIT>
__device__ __forceinline__ void qk_mma(float (&s)[48], const uint32_t (&qf)[48], uint32_t box0, uint32_t box1, uint32_t box2, int pass_id) {
  const uint32_t d0 = desc_lo(box0, 16), d1 = desc_lo(box1, 16), d2 = desc_lo(box2, 16);
  if (INIT) wgmma_rs_n96_tb0_init(s, qf[0], qf[1], qf[2], qf[3], desc(d0));
  else      wgmma_rs_n96_tb0(s, qf[0], qf[1], qf[2], qf[3], desc(d0));
#pragma unroll
  for (int k = 1; k < 12; k++) {
    wgmma_rs_n96_tb0(s, qf[4 * k], qf[4 * k + 1], qf[4 * k + 2], qf[4 * k + 3], desc(k < 4 ? d0 : k < 8 ? d1 : d2, (k & 3) * 32));
  }
  tok_pass(pass_id);
}
template <bool INIT>
__device__ __forceinline__ void pv_mma(float (&o)[96], const uint32_t (&pf)[24], uint32_t box01, uint32_t box2, int pass_id) {
  float (&oa)[64] = *reinterpret_cast<float (*)[64]>(&o[0]);
  float (&ob)[32] = *reinterpret_cast<float (*)[32]>(&o[64]);
  const uint32_t da = desc_lo(box01, 12288), db = desc_lo(box2, 12288);
  if (INIT) { wgmma_rs_n128_tb1_init(oa, pf[0], pf[1], pf[2], pf[3], desc(da)); wgmma_rs_n64_tb1_init(ob, pf[0], pf[1], pf[2], pf[3], desc(db)); }
  else      { wgmma_rs_n128_tb1(oa, pf[0], pf[1], pf[2], pf[3], desc(da));      wgmma_rs_n64_tb1(ob, pf[0], pf[1], pf[2], pf[3], desc(db)); }
#pragma unroll
  for (int k = 1; k < 6; k++) {
    wgmma_rs_n128_tb1(oa, pf[4 * k], pf[4 * k + 1], pf[4 * k + 2], pf[4 * k + 3], desc(da, k * 2048));
    wgmma_rs_n64_tb1(ob, pf[4 * k], pf[4 * k + 1], pf[4 * k + 2], pf[4 * k + 3], desc(db, k * 2048));
  }
  tok_pass(pass_id);
}

__global__ void __cluster_dims__(2, 1, 1) __launch_bounds__(NTHREADS, 1)
fused_attn_kernel(const __grid_constant__ Params prm) {
  extern __shared__ uint8_t smem_raw[];
  __shared__ uint64_t s_bars[3 * NSLOT + 11];
  __shared__ uint32_t s_dummy[64];
  __shared__ volatile uint32_t s_prog;

  const uint32_t ring = (smem_u32(smem_raw) + 1023) & ~1023u;
  const uint32_t stg  = ring + NSLOT * SLOT_BYTES;
  const uint32_t full0 = smem_u32(&s_bars[0]);
  const uint32_t o_done  = full0 + 24 * NSLOT;
  const uint32_t x_free  = o_done + 80;
  const uint32_t o_ready = o_done + 48;

  const int tid = threadIdx.x, lane = tid & 31;
  const int warp = __shfl_sync(0xffffffffu, tid >> 5, 0);
  const int rank = blockIdx.x & 1, cl = logical_cluster(blockIdx.x >> 1), cta = 2 * cl + rank;
  const int grp = cl >> 3, prob = grp >> 2, bp = grp & 3, j8 = cl & 7;
  const int split = j8 >> 1;

  if (tid == 13 * 32) {
    asm volatile("prefetch.tensormap [%0];" :: "l"(&prm.wq[prob]) : "memory");
    asm volatile("prefetch.tensormap [%0];" :: "l"(&prm.x1[prob]) : "memory");
    asm volatile("prefetch.tensormap [%0];" :: "l"(&prm.x[prob]) : "memory");
  }
  if (tid == 12 * 32) {
#pragma unroll
    for (int s = 0; s < NSLOT; s++) { mbar_init(full0 + 8 * s, 1); mbar_init(full0 + 8 * NSLOT + 8 * s, 3); mbar_init(full0 + 16 * NSLOT + 8 * s, 3); }
    for (int s = 0; s < 6; s++) mbar_init(o_done + 8 * s, 12);
    for (int s = 0; s < 4; s++) mbar_init(o_ready + 8 * s, 1);
    mbar_init(x_free, 3);
    s_prog = NSLOT;
    asm volatile("fence.mbarrier_init.release.cluster;" ::: "memory");
  }
  __syncthreads();
  cluster_arrive_relaxed();
  if (tid == 12 * 32) {
    const int h = 2 * j8 + rank;
    const uint64_t pol = policy_evict_first();
#pragma unroll
    for (int s = 0; s < NSLOT; s++) {
      mbar_expect_tx(full0 + 8 * s, SLOT_BYTES);
      tma_2d_nohint(ring + s * SLOT_BYTES, &prm.x1[prob], full0 + 8 * s, 64 * s, 192 * bp);
      tma_3d(ring + s * SLOT_BYTES + B_OFF, &prm.wq[prob], full0 + 8 * s, 0, 64 * s, 3 * h, pol);
    }
  }
  __syncwarp();
  cluster_wait();

  if (warp >= 12) {
    asm volatile("setmaxnreg.dec.sync.aligned.u32 32;");
    if (warp == 12) {
      if (lane == 0) {
        Ring r{0};
        const uint64_t pol_s = policy_evict_first();
        const int ncol0 = 320 * (j8 & 1);
#pragma unroll 1
        for (int w = 0; w < 2; w++) {
          const int h = 16 * w + 2 * j8 + rank;
#pragma unroll 1
          for (int ks = 0; ks < 10; ks++) {
            const uint32_t fb = r.full(full0), sl = r.addr(ring);
            if (r.u >= NSLOT) {
              mbar_wait(r.empty(full0), r.phase() ^ 1);
              mbar_expect_tx(fb, SLOT_BYTES);
              s_prog = r.u;
              tma_3d(sl + B_OFF, &prm.wq[prob], fb, 0, 64 * ks, 3 * h, pol_s);
              mbar_wait(r.empty(full0) + 8 * NSLOT, r.phase() ^ 1);
              tma_2d_mc(sl + rank * 12288, &prm.x[prob], fb, 64 * ks, 192 * bp + 96 * rank);
            }
            r.u++;
          }
#pragma unroll 1
          for (int t = 0; t < 3; t++) {
            const uint32_t fb = r.full(full0), sl = r.addr(ring);
            const int row0 = ((2 * bp) * 32 + h) * 96, row1 = row0 + 32 * 96;
            mbar_wait(r.empty(full0), r.phase() ^ 1);
            mbar_expect_tx(fb, SLOT_BYTES);
            s_prog = r.u;
            if (t == 0) {
              tma_3d(sl,         &prm.k[prob],  fb, 0, row0, 0, pol_s);
              tma_3d(sl + 36864, &prm.k1[prob], fb, 0, row1, 0, pol_s);
            } else if (t == 1) {
              tma_3d(sl,         &prm.k1[prob], fb, 0, row1, 1, pol_s);
              tma_3d(sl + 12288, &prm.k1[prob], fb, 0, row1, 2, pol_s);
              tma_3d(sl + 24576, &prm.v1[prob], fb, 0, row0, 0, pol_s);
              tma_3d(sl + 36864, &prm.v1[prob], fb, 0, row0, 1, pol_s);
            } else {
              tma_3d(sl,         &prm.v1[prob], fb, 0, row0, 2, pol_s);
              tma_3d(sl + 12288, &prm.v[prob],  fb, 0, row1, 0, pol_s);
            }
            mbar_wait(r.empty(full0) + 8 * NSLOT, r.phase() ^ 1);
            r.u++;
          }
        }
#pragma unroll 1
        for (int i = 0; i < 24; i++) {
          const int h = i < 12 ? 4 * split + i / 3 : 16 + 4 * split + (i & 3);
          const int c = i < 12 ? i % 3 : (i - 12) >> 2;
          const uint32_t fb = r.full(full0), sl = r.addr(ring);
          const int k0 = h * 192 + c * 64;
          mbar_wait(r.empty(full0), r.phase() ^ 1);
          mbar_expect_tx(fb, SLOT_BYTES);
          s_prog = r.u;
          tma_2d(sl + B_OFF,         &prm.wo[prob],   fb, ncol0 + 192 * rank,      k0, pol_s);
          tma_2d(sl + B_OFF + 8192,  &prm.wo[prob],   fb, ncol0 + 192 * rank + 64, k0, pol_s);
          tma_2d(sl + B_OFF + 16384, &prm.wo[prob],   fb, ncol0 + 128, k0, pol_s);
          if (i == 0 || (i >= 12 && (i & 3) == 0)) {
            mbar_wait(o_ready + 8 * (i == 0 ? 0 : (i >> 2) - 2), 0);
          }
          mbar_wait(r.empty(full0) + 8 * NSLOT, r.phase() ^ 1);
          tma_2d_mc(sl + rank * 12288, &prm.o_ld, fb, k0, prob * 768 + 192 * bp + 96 * rank);
          r.u++;
        }
      }
    } else if (warp == 13) {
      {
        const unsigned obase = 3u * ld_relaxed(&prm.epoch[cta]);
        uint32_t pub = 0, wat = 0;
#pragma unroll 1
        for (int it = 0; it < (1 << 22) && (pub < 6 || wat < 4); it++) {
          if (pub < 6 && mbar_test(o_done + 8 * pub, 0)) {
            uint32_t n = 1;
            while ((pub + n) % 3 != 0 && mbar_test(o_done + 8 * (pub + n), 0)) n++;
            if (lane == 0) {
              asm volatile("red.relaxed.gpu.global.add.u32 [%0], %1;"
                           :: "l"(&prm.ready[grp * 32 + 16 * (pub >= 3) + 2 * j8 + rank]), "r"(n) : "memory");
            }
            __syncwarp();
            pub += n;
          } else if (wat < 4 && pub > wat + 2) {
            const unsigned tgt = obase + (wat == 0 ? 3u : wat);
            const unsigned a = ld_acquire(&prm.ready[grp * 32 + (wat == 0 ? 0 : 16) + 4 * split + (lane & 3)]);
            if (__all_sync(0xffffffffu, (int)(a - tgt) >= 0)) {
              if (lane == 0) {
                asm volatile("fence.proxy.async;" ::: "memory");
                mbar_arrive(o_ready + 8 * wat);
              }
              __syncwarp();
              wat++;
            }
          } else {
            mbar_wait(o_done + 8 * pub, 0);
          }
        }
      }
    } else {
      const int h0 = 2 * j8 + rank;
      const uint8_t* wqp = prm.wqptr[prob];
      auto addr_of = [&](int n) -> const uint8_t* {
        if (n < 9 || (n >= 45 && n < 60)) {
          const bool second = n >= 45;
          const int i = (second ? n - 45 : n + 6) * 32 + lane;
          const int ks = i / 48, rem = i - ks * 48;
          return wqp + (size_t)(64 * ks + 16 * bp + rem / 3) * 12288 + (h0 + (second ? 16 : 0)) * 384 + (rem % 3) * 128;
        }
        const bool second = n >= 60;
        const int m = second ? n - 60 : n - 9, tile = m / 9;
        const uint8_t* base = (tile < 2) ? prm.kptr[prob] : prm.vptr[prob];
        return base + (size_t)((2 * bp + (tile & 1)) * 32 + h0 + (second ? 16 : 0)) * KV_BYTES + (m - 9 * tile) * 4096 + lane * 128;
      };
      auto use_of = [&](int n) -> int {
        if (n < 9)  return ((n + 6) * 32) / 48;
        if (n < 45) { const int t = (n - 9) / 9; return 10 + (t < 2 ? 0 : t - 1); }
        if (n < 60) return 13 + ((n - 45) * 32) / 48;
        const int t = (n - 60) / 9;
        return 23 + (t < 2 ? 0 : t - 1);
      };
      auto release_of = [&](int n) -> int {
        if (n < 9)  return 0;
        if (n < 45) return PF_R0 + ((n - 9) * (PF_R1 - PF_R0)) / 36;
        if (n < 60) return PF_R1 + ((n - 45) * (PF_R2 - PF_R1)) / 15;
        return PF_R2 + ((n - 60) * (PF_R3 - PF_R2)) / 36;
      };
      const uint32_t dummy = smem_u32(&s_dummy[tid & 63]);
#pragma unroll 1
      for (int n = warp - 14; n < 96; n += 2) {
        const int u = use_of(n), rel = release_of(n);
        int guard = 0;
        while ((int)s_prog < rel && ++guard < (1 << 20)) __nanosleep(100);
        if ((int)s_prog < u)
          asm volatile("cp.async.ca.shared.global.L2::128B [%0], [%1], 4;" :: "r"(dummy), "l"(addr_of(n)) : "memory");
        asm volatile("cp.async.commit_group;" ::: "memory");
        asm volatile("cp.async.wait_group %0;" :: "n"(PF_WIN) : "memory");
      }
      asm volatile("cp.async.wait_group 0;" ::: "memory");
    }
  } else {
    asm volatile("setmaxnreg.inc.sync.aligned.u32 160;");
    const int wg = warp >> 2, wq4 = warp & 3;
    const bool elected = wq4 == 0 && lane_id() == 0;
    const uint32_t descA0 = desc_lo(ring + wg * 8192, 16), descB0 = desc_lo(ring + B_OFF, 8192);
    Ring r{0};
    uint32_t pend[32];
    const uint32_t wstg = stg + warp * 2048;
    auto stg_acquire = [&]() {
      if (lane_id() == 0) asm volatile("cp.async.bulk.wait_group.read 0;" ::: "memory");
      __syncwarp();
    };
    auto stage_in = [&](const uint32_t* v) {
      stg_acquire();
      const int lane = lane_id(), r8 = lane & 7;
      const uint32_t st_base = wstg + (((lane >> 3) & 1) * 8 + r8) * 128;
#pragma unroll
      for (int jj = 0; jj < 4; jj++) {
        const uint32_t addr = st_base + (((2 * jj + (lane >> 4)) ^ r8) << 4);
        asm volatile("stmatrix.sync.aligned.m8n8.x4.shared.b16 [%0], {%1, %2, %3, %4};"
                     :: "r"(addr), "r"(v[4 * jj]), "r"(v[4 * jj + 1]), "r"(v[4 * jj + 2]), "r"(v[4 * jj + 3]) : "memory");
      }
    };
    auto send = [&](int wv, int box) {
      asm volatile("fence.proxy.async.shared::cta;" ::: "memory");
      __syncwarp();
      if (lane_id() == 0) {
        tma_store_2d(&prm.o_st, wstg, (16 * wv + 2 * j8 + rank) * 192 + 64 * box, prob * 768 + 192 * bp + 16 * warp);
        asm volatile("cp.async.bulk.commit_group;" ::: "memory");
      }
    };
    auto landed = [&](int ev, auto pending) {
      if (lane_id() == 0) {
        asm volatile("cp.async.bulk.wait_group %0;" :: "n"(decltype(pending)::value) : "memory");
        mbar_arrive(o_done + 8 * ev);
      }
    };

#pragma unroll 1
    for (int w = 0; w < 2; w++) {
      uint32_t qf[48];
      {
        float acc[96];
        {
          const uint32_t da = descA0 + r.slot() * (SLOT_BYTES >> 4), db = descB0 + r.slot() * (SLOT_BYTES >> 4);
          mbar_wait(r.full(full0), r.phase());
          if (w > 0) { if (wg == 0) tok_wait(14); else if (wg == 2) tok_wait(15); }
          wg_fence();
          wgmma_ss_n192_tb1_init(acc, desc(da), desc(db));
#pragma unroll
          for (int k = 1; k < 4; k++) wgmma_ss_n192_tb1(acc, desc(da, k * 32), desc(db, k * 2048));
          wg_commit();
          if (w > 0 && wg == 0) tok_pass(15);
          if (w > 0) send(0, 0);
          r.u++;
        }
#pragma unroll 1
        for (int ks = 1; ks < 8; ks++) {
          const uint32_t da = descA0 + r.slot() * (SLOT_BYTES >> 4), db = descB0 + r.slot() * (SLOT_BYTES >> 4);
          mbar_wait(r.full(full0), r.phase());
          wg_fence();
          wgmma_ss_n192_tb1(acc, desc(da), desc(db));
          wg_commit();
          wg_wait<1>();
          if (elected) mbar_arrive_both(Ring{r.u - 1}.empty(full0), rank ^ 1);
#pragma unroll
          for (int k = 1; k < 4; k++) wgmma_ss_n192_tb1(acc, desc(da, k * 32), desc(db, k * 2048));
          wg_commit();
          if (w > 0) {
            if (ks == FL_B1)      { stage_in(pend);      send(0, 1); }
            else if (ks == FL_B2) { stage_in(pend + 16); send(0, 2); }
            else if (ks == FL_LD) { landed(0, Int<0>{}); landed(1, Int<0>{}); landed(2, Int<0>{}); }
          }
          r.u++;
        }
        {
          const Ring r8 = r, r9 = r + 1;
          r.u += 2;
          wg_wait<0>();
          if (elected) mbar_arrive_both(Ring{r8.u - 1}.empty(full0), rank ^ 1);
          mbar_wait(r8.full(full0), r8.phase());
          mbar_wait(r9.full(full0), r9.phase());
          if (wg != 1) tok_wait(wg == 0 ? 4 : 5);
          const uint32_t da8 = descA0 + r8.slot() * (SLOT_BYTES >> 4), db8 = descB0 + r8.slot() * (SLOT_BYTES >> 4);
          const uint32_t da9 = descA0 + r9.slot() * (SLOT_BYTES >> 4), db9 = descB0 + r9.slot() * (SLOT_BYTES >> 4);
          wg_fence();
#pragma unroll
          for (int k = 0; k < 4; k++) wgmma_ss_n192_tb1(acc, desc(da8, k * 32), desc(db8, k * 2048));
          wg_commit();
#pragma unroll
          for (int k = 0; k < 4; k++) wgmma_ss_n192_tb1(acc, desc(da9, k * 32), desc(db9, k * 2048));
          wg_commit();
          if (wg != 2) tok_pass(wg == 1 ? 4 : 5);
          wg_wait<1>();
          if (elected) mbar_arrive_both(r8.empty(full0), rank ^ 1);
          mbar_wait(r.full(full0), r.phase());
          if (wg == 2) mbar_wait((r + 1).full(full0), (r + 1).phase());
          wg_wait<0>();
          if (elected) mbar_arrive_both(r9.empty(full0), rank ^ 1);
        }
        stg_acquire();
        const int lane = lane_id();
#pragma unroll
        for (int i = 0; i < 4; i++)
          asm volatile("st.shared.v4.u32 [%0], {%1, %2, %3, %4};"
                       :: "r"(wstg + i * 512 + lane * 16),
                          "r"(pack_bf16(acc[64 + 8 * i], acc[65 + 8 * i])), "r"(pack_bf16(acc[66 + 8 * i], acc[67 + 8 * i])),
                          "r"(pack_bf16(acc[68 + 8 * i], acc[69 + 8 * i])), "r"(pack_bf16(acc[70 + 8 * i], acc[71 + 8 * i])) : "memory");
#pragma unroll
        for (int i = 0; i < 32; i++) qf[i] = pack_bf16(acc[2 * i], acc[2 * i + 1]);
        asm volatile("" ::: "memory");
#pragma unroll
        for (int i = 0; i < 4; i++)
          asm volatile("ld.shared.v4.u32 {%0, %1, %2, %3}, [%4];"
                       : "=r"(qf[32 + 4 * i]), "=r"(qf[33 + 4 * i]), "=r"(qf[34 + 4 * i]), "=r"(qf[35 + 4 * i])
                       : "r"(wstg + i * 512 + lane * 16) : "memory");
      }
      const Ring rX = r, rY = r + 1, rZ = r + 2;
      r.u += 3;
      uint32_t pf[24];
      float rinv0, rinv1;
      bool z_ready;
      const uint32_t aX = rX.addr(ring), aY = rY.addr(ring), aZ = rZ.addr(ring);
      {
        float s[48];
        if (wg != 1) tok_wait(wg == 0 ? 7 : 9);
        wg_fence();
        qk_mma<true>(s, qf, wg == 2 ? aX + 36864 : aX, wg == 2 ? aY : aX + 12288, wg == 2 ? aY + 12288 : aX + 24576, wg == 1 ? 7 : wg == 0 ? 8 : 10);
        wg_commit();
        if (wg != 2) mbar_wait(rY.full(full0), rY.phase());
        wg_wait<0>();
        if (wg == 1) {
          if (wq4 < 2) {
#pragma unroll
            for (int i = 0; i < 48; i++) qf[i] = 0u;
          } else {
#pragma unroll
            for (int i = 0; i < 48; i++) s[i] = 0.f;
          }
          tok_wait(8);
          wg_fence();
          qk_mma<false>(s, qf, aX + 36864, aY, aY + 12288, 9);
          wg_commit();
          wg_wait<0>();
        }
        if (elected) { mbar_arrive_both(rX.empty(full0), rank ^ 1); if (wg == 2) mbar_arrive_both(rY.empty(full0), rank ^ 1); }
        __syncwarp();
        z_ready = mbar_test(rZ.full(full0), rZ.phase());
        softmax96(s, pf, rinv0, rinv1);
      }
      float o[96];
      {
        if (!__all_sync(0xffffffffu, z_ready)) mbar_wait(rZ.full(full0), rZ.phase());
        tok_wait(wg == 0 ? 10 : wg == 1 ? 11 : 12);
        wg_fence();
        pv_mma<true>(o, pf, wg == 2 ? aZ + 12288 : aY + 24576, wg == 2 ? aZ + 36864 : aZ, wg == 0 ? 11 : wg == 1 ? 12 : 13);
        wg_commit();
        wg_wait<0>();
        if (wg == 1) {
          if (elected) mbar_arrive_both(rY.empty(full0), rank ^ 1);
          if (wq4 < 2) {
#pragma unroll
            for (int i = 0; i < 24; i++) pf[i] = 0u;
          } else {
#pragma unroll
            for (int i = 0; i < 96; i++) o[i] = 0.f;
          }
          tok_wait(13);
          wg_fence();
          pv_mma<false>(o, pf, aZ + 12288, aZ + 36864, 14);
          wg_commit();
          wg_wait<0>();
        }
        if (elected) { if (wg == 0) mbar_arrive_both(rY.empty(full0), rank ^ 1); mbar_arrive_both(rZ.empty(full0), rank ^ 1); }
      }
      {
        uint32_t v[16];
#pragma unroll
        for (int i = 0; i < 16; i++) { const float ri = (i & 1) ? rinv1 : rinv0; v[i] = pack_bf16(o[2 * i] * ri, o[2 * i + 1] * ri); }
#pragma unroll
        for (int i = 0; i < 32; i++) { const float ri = (i & 1) ? rinv1 : rinv0; pend[i] = pack_bf16(o[32 + 2 * i] * ri, o[33 + 2 * i] * ri); }
        stage_in(v);
      }
    }

    const unsigned otarget = ld_relaxed(&prm.epoch[cta]) + 1u, target = 3u * otarget;
    const uint32_t bhi = 0x40000040u | (rank ? 4u << 17 : 0u);
    float acc[80];
    {
      {
        const uint32_t da = descA0 + r.slot() * (SLOT_BYTES >> 4), db = descB0 + r.slot() * (SLOT_BYTES >> 4);
        mbar_wait(r.full(full0), r.phase());
        if (wg == 0) tok_wait(14); else if (wg == 2) tok_wait(15);
        wg_fence();
        wgmma_ss_n160_tb1_init(acc, desc(da), desc(db, 0, bhi));
#pragma unroll
        for (int k = 1; k < 4; k++) wgmma_ss_n160_tb1(acc, desc(da, k * 32), desc(db, k * 2048, bhi));
        wg_commit();
        if (wg == 0) tok_pass(15);
        send(1, 0);
        r.u++;
      }
#pragma unroll 1
      for (int ks = 1; ks < 24 - TAIL_L; ks++) {
        const uint32_t da = descA0 + r.slot() * (SLOT_BYTES >> 4), db = descB0 + r.slot() * (SLOT_BYTES >> 4);
        mbar_wait(r.full(full0), r.phase());
        wg_fence();
        wgmma_ss_n160_tb1(acc, desc(da), desc(db, 0, bhi));
        wg_commit();
        wg_wait<1>();
        if (elected) mbar_arrive_both(Ring{r.u - 1}.empty(full0), rank ^ 1);
#pragma unroll
        for (int k = 1; k < 4; k++) wgmma_ss_n160_tb1(acc, desc(da, k * 32), desc(db, k * 2048, bhi));
        wg_commit();
        {
          if (ks == FL2_B1)      { landed(3, Int<0>{}); stage_in(pend);      send(1, 1); }
          else if (ks == FL2_B2) { landed(4, Int<0>{}); stage_in(pend + 16); send(1, 2); }
          else if (ks == FL2_LD) { landed(5, Int<0>{}); }
        }
        r.u++;
      }
      static_assert(TAIL_L == NSLOT - 1, "the slots of the last NSLOT ring uses are not released");
      if (wg > 0) {
        wg_wait<0>();
        if (elected) mbar_arrive(x_free);
#pragma unroll
        for (int i = 0; i < TAIL_L; i++) mbar_wait((r + i).full(full0), (r + i).phase());
        tok_wait(3 + wg);
      } else {
        mbar_wait(r.full(full0), r.phase());
        mbar_wait((r + 1).full(full0), (r + 1).phase());
      }
      wg_fence();
#pragma unroll
      for (int i = 0; i < TAIL_L; i++) {
        const uint32_t da = descA0 + (r + i).slot() * (SLOT_BYTES >> 4), db = descB0 + (r + i).slot() * (SLOT_BYTES >> 4);
        if (i == TAIL_L - 1 && wg == 0) mbar_wait((r + i).full(full0), (r + i).phase());
#pragma unroll
        for (int k = 0; k < 4; k++) wgmma_ss_n160_tb1(acc, desc(da, k * 32), desc(db, k * 2048, bhi));
      }
      wg_commit();
      if (wg < 2) tok_pass(4 + wg);
      wg_wait<0>();
      if (wg == 0 && elected) mbar_arrive(x_free);
    }
    {
      const int lane = lane_id(), t = warp * 32 + lane;
      const uint32_t xstg = Ring{r.u - 1}.addr(ring) + warp * 4096;
      mbar_wait(x_free, 0);
#pragma unroll
      for (int q = 0; q < 4; q++) {
        const int blk0 = q == 0 ? 0 : q == 1 ? 6 : q == 2 ? 10 : 16, npk = (q & 1) ? 2 : 3;
        const int cum = q == 0 ? 0 : q == 1 ? 3 : q == 2 ? 5 : 8;
        if (q != split) {
          const uint32_t dst = xstg + (cum - (split < q ? ((split & 1) ? 2 : 3) : 0)) * 512 + lane * 16;
#pragma unroll
          for (int i = 0; i < 3; i++) {
            if (i < npk) {
              const int a = 4 * blk0 + 8 * i;
              asm volatile("st.shared.v4.u32 [%0], {%1, %2, %3, %4};"
                           :: "r"(dst + i * 512), "r"(pack_bf16(acc[a], acc[a + 1])), "r"(pack_bf16(acc[a + 2], acc[a + 3])),
                              "r"(pack_bf16(acc[a + 4], acc[a + 5])), "r"(pack_bf16(acc[a + 6], acc[a + 7])) : "memory");
            }
          }
        }
      }
      asm volatile("fence.proxy.async.shared::cta;" ::: "memory");
      __syncwarp();
      if (lane == 0) {
#pragma unroll
        for (int q = 0; q < 4; q++) {
          const int npk = (q & 1) ? 2 : 3, cum = q == 0 ? 0 : q == 1 ? 3 : q == 2 ? 5 : 8;
          if (q != split) {
            const int dcta = (grp * 8 + 2 * q + (j8 & 1)) * 2 + rank;
            const int srcslot = split < q ? split : split - 1;
            asm volatile("cp.async.bulk.global.shared::cta.bulk_group [%0], [%1], %2;"
                         :: "l"(prm.part + ((size_t)(dcta * 3 + srcslot) * 12 + warp) * 96),
                            "r"(xstg + (cum - (split < q ? ((split & 1) ? 2 : 3) : 0)) * 512), "r"(npk * 512) : "memory");
          }
        }
        asm volatile("cp.async.bulk.commit_group;" ::: "memory");
        asm volatile("cp.async.bulk.wait_group 0;" ::: "memory");
#pragma unroll
        for (int q = 0; q < 4; q++) {
          if (q != split)
            asm volatile("red.relaxed.gpu.global.add.u32 [%0], %1;"
                         :: "l"(&prm.xflag[((grp * 8 + 2 * q + (j8 & 1)) * 2 + rank) * 12 + warp]), "r"(1u) : "memory");
        }
      }
      __syncwarp();
      const int nown = (split & 1) ? 2 : 3;
      float own[24];
#pragma unroll
      for (int i = 0; i < 24; i++)
        own[i] = split == 0 ? acc[i] : split == 1 ? acc[24 + (i & 15)] : split == 2 ? acc[40 + i] : acc[64 + (i & 15)];
      spin_until(&prm.xflag[cta * 12 + warp], target);
      {
        const uint4* src = prm.part + ((size_t)(cta * 3) * 12 + warp) * 96 + lane;
        uint4 v[9];
#pragma unroll
        for (int sidx = 0; sidx < 3; sidx++) {
          v[3 * sidx]     = __ldcg(src + sidx * (12 * 96));
          v[3 * sidx + 1] = __ldcg(src + sidx * (12 * 96) + 32);
          v[3 * sidx + 2] = nown == 3 ? __ldcg(src + sidx * (12 * 96) + 64) : make_uint4(0u, 0u, 0u, 0u);
        }
#pragma unroll
        for (int sidx = 0; sidx < 3; sidx++) {
#pragma unroll
          for (int i = 0; i < 3; i++) {
            const uint32_t w[4] = {v[3 * sidx + i].x, v[3 * sidx + i].y, v[3 * sidx + i].z, v[3 * sidx + i].w};
#pragma unroll
            for (int k = 0; k < 4; k++) {
              own[8 * i + 2 * k]     += __uint_as_float(w[k] << 16);
              own[8 * i + 2 * k + 1] += __uint_as_float(w[k] & 0xffff0000u);
            }
          }
        }
      }
      stg_acquire();
      {
        const uint32_t st_base = wstg + (((lane >> 3) & 1) * 8 + (lane & 7)) * 32 + (lane >> 4) * 16;
#pragma unroll
        for (int jj = 0; jj < 3; jj++) {
          asm volatile("stmatrix.sync.aligned.m8n8.x4.shared.b16 [%0], {%1, %2, %3, %4};"
                       :: "r"(st_base + jj * 512), "r"(pack_bf16(own[8 * jj], own[8 * jj + 1])), "r"(pack_bf16(own[8 * jj + 2], own[8 * jj + 3])),
                          "r"(pack_bf16(own[8 * jj + 4], own[8 * jj + 5])), "r"(pack_bf16(own[8 * jj + 6], own[8 * jj + 7])) : "memory");
        }
        asm volatile("fence.proxy.async.shared::cta;" ::: "memory");
        __syncwarp();
        if (lane == 0) {
          const int a0 = split == 0 ? 0 : split == 1 ? 48 : split == 2 ? 80 : 128;
#pragma unroll
          for (int u = 0; u < 3; u++) {
            if (u < nown) {
              const int a = a0 + 16 * u;
              const int col = rank == 0 ? a : (a < 128 ? 192 + (a ^ 32) : 32 + a);
              tma_store_2d(&prm.out_st, wstg + u * 512, 640 * prob + 320 * (j8 & 1) + col, 192 * bp + 16 * warp);
            }
          }
          asm volatile("cp.async.bulk.commit_group;" ::: "memory");
          asm volatile("cp.async.bulk.wait_group.read 0;" ::: "memory");
        }
      }
      if (t == 0) prm.epoch[cta] = otarget;
    }
  }
}

typedef CUresult (*EncodeFn)(CUtensorMap*, CUtensorMapDataType, cuuint32_t, void*, const cuuint64_t*, const cuuint64_t*,
                             const cuuint32_t*, const cuuint32_t*, CUtensorMapInterleave, CUtensorMapSwizzle,
                             CUtensorMapL2promotion, CUtensorMapFloatOOBfill);

void make_map(EncodeFn enc, CUtensorMap* m, const void* ptr, int rank, const uint64_t* dims, const uint64_t* strides,
              const uint32_t* box, CUtensorMapSwizzle swz = CU_TENSOR_MAP_SWIZZLE_128B) {
  cuuint64_t d[3], s[2]; cuuint32_t b[3], e[3] = {1, 1, 1};
  for (int i = 0; i < rank; i++) { d[i] = dims[i]; b[i] = box[i]; }
  for (int i = 0; i + 1 < rank; i++) s[i] = strides[i];
  enc(m, CU_TENSOR_MAP_DATA_TYPE_BFLOAT16, rank, const_cast<void*>(ptr), d, s, b, e, CU_TENSOR_MAP_INTERLEAVE_NONE,
      swz, CU_TENSOR_MAP_L2_PROMOTION_L2_128B, CU_TENSOR_MAP_FLOAT_OOB_FILL_NONE);
}

}

extern "C" void kernel_launch(void* const* d_in, const int* in_sizes, int n_in, void* d_out, int out_size) {
  (void)in_sizes; (void)n_in; (void)out_size;
  static EncodeFn enc = nullptr;
  static void *o_ptr = nullptr, *part_ptr = nullptr, *ready_ptr = nullptr, *xflag_ptr = nullptr, *epoch_ptr = nullptr;
  if (!enc) {
    void* fn = nullptr; cudaDriverEntryPointQueryResult st;
    cudaGetDriverEntryPoint("cuTensorMapEncodeTiled", &fn, cudaEnableDefault, &st);
    enc = (EncodeFn)fn;
    cudaGetSymbolAddress(&o_ptr, g_O);
    cudaGetSymbolAddress(&part_ptr, g_part);
    cudaGetSymbolAddress(&ready_ptr, g_ready);
    cudaGetSymbolAddress(&xflag_ptr, g_xflag);
    cudaGetSymbolAddress(&epoch_ptr, g_epoch);
    cudaFuncSetAttribute(fused_attn_kernel, cudaFuncAttributeMaxDynamicSharedMemorySize, SMEM_BYTES);
  }
  Params prm;
  for (int p = 0; p < 2; p++) {
    const void* x = d_in[5 * p + 0]; const void* k = d_in[5 * p + 1]; const void* v = d_in[5 * p + 2];
    const void* wq = d_in[5 * p + 3]; const void* wo = d_in[5 * p + 4];
    { uint64_t d[2] = {640, 768}, s[1] = {1280};              uint32_t b[2] = {64, 96};    make_map(enc, &prm.x[p],  x,  2, d, s, b); }
    { uint64_t d[2] = {640, 768}, s[1] = {1280};              uint32_t b[2] = {64, 192};   make_map(enc, &prm.x1[p], x,  2, d, s, b); }
    { uint64_t d[3] = {64, 640, 96}, s[2] = {12288, 128};     uint32_t b[3] = {64, 64, 3}; make_map(enc, &prm.wq[p], wq, 3, d, s, b); }
    { uint64_t d[3] = {64, 24576, 3}, s[2] = {384, 128};      uint32_t b[3] = {64, 96, 3}; make_map(enc, &prm.k[p],  k,  3, d, s, b); }
    { uint64_t d[3] = {64, 24576, 3}, s[2] = {384, 128};      uint32_t b[3] = {64, 96, 1}; make_map(enc, &prm.k1[p], k,  3, d, s, b); }
    { uint64_t d[3] = {64, 24576, 3}, s[2] = {384, 128};      uint32_t b[3] = {64, 96, 3}; make_map(enc, &prm.v[p],  v,  3, d, s, b); }
    { uint64_t d[3] = {64, 24576, 3}, s[2] = {384, 128};      uint32_t b[3] = {64, 96, 1}; make_map(enc, &prm.v1[p], v,  3, d, s, b); }
    prm.kptr[p] = (const uint8_t*)k; prm.vptr[p] = (const uint8_t*)v;
    prm.wqptr[p] = (const uint8_t*)wq;
    { uint64_t d[2] = {640, 6144}, s[1] = {1280};             uint32_t b[2] = {64, 64};    make_map(enc, &prm.wo[p], wo, 2, d, s, b); }
  }
  { uint64_t d[2] = {6144, 1536}, s[1] = {12288};        uint32_t b[2] = {64, 16};    make_map(enc, &prm.o_st, o_ptr, 2, d, s, b); }
  { uint64_t d[2] = {6144, 1536}, s[1] = {12288};        uint32_t b[2] = {64, 96};    make_map(enc, &prm.o_ld, o_ptr, 2, d, s, b); }
  { uint64_t d[2] = {1280, 768}, s[1] = {2560};          uint32_t b[2] = {16, 16};    make_map(enc, &prm.out_st, d_out, 2, d, s, b, CU_TENSOR_MAP_SWIZZLE_NONE); }
  prm.part = (uint4*)part_ptr; prm.ready = (unsigned*)ready_ptr; prm.xflag = (unsigned*)xflag_ptr; prm.epoch = (unsigned*)epoch_ptr;
  fused_attn_kernel<<<128, NTHREADS, SMEM_BYTES>>>(prm);
}
```

```cpp
#include <cuda_runtime.h>
#include <cuda_bf16.h>
#include <cuda.h>
#include <stdint.h>

namespace {

constexpr int FL_B1 = 2,  FL_B2 = 5,  FL_LD = 7;
constexpr int FL2_B1 = 2, FL2_B2 = 5, FL2_LD = 8;
constexpr int TAIL_L = 3;
constexpr int PF_WIN = 10;
constexpr int PF_R0 = 0, PF_R1 = 8, PF_R2 = 11, PF_R3 = 21;

constexpr int NTHREADS   = 512;
constexpr int NSLOT      = 4;
constexpr int SLOT_BYTES = 49152;
constexpr int B_OFF      = 24576;
constexpr int KV_BYTES   = 36864;
constexpr int STG_BYTES  = 12 * 2048;
constexpr int SMEM_BYTES = NSLOT * SLOT_BYTES + STG_BYTES + 1024  ;

struct Params {
  CUtensorMap x[2], x1[2], wq[2], k[2], k1[2], v[2], v1[2], wo[2];
  CUtensorMap o_st, o_ld, out_st;
  const uint8_t* kptr[2];
  const uint8_t* vptr[2];
  const uint8_t* wqptr[2];
  uint4*    part;
  unsigned* ready;
  unsigned* xflag;
  unsigned* epoch;
};

__host__ __device__ __forceinline__ int logical_cluster(int c) {
  const unsigned tab = 0xE6CA8421u;
  int v, bp;
  if (c < 4)       { v = 0; bp = c; }
  else if (c < 36) { const int t = c - 4;  v = (tab >> (4 * (t & 7))) & 15;          bp = t >> 3; }
  else             { const int t = c - 36; v = ((tab >> (4 * (1 + t % 7))) & 15) + 1; bp = t / 7; }
  return (v >> 3) * 32 + bp * 8 + (v & 7);
}

__device__ __nv_bfloat16 g_O[1536 * 6144];
__device__ uint4         g_part[128 * 3 * 3 * 384];
__device__ unsigned      g_ready[8 * 32];
__device__ unsigned      g_xflag[128 * 12];
__device__ unsigned      g_epoch[128];

__device__ __forceinline__ uint32_t smem_u32(const void* p) { return (uint32_t)__cvta_generic_to_shared(p); }
__device__ __forceinline__ void mbar_init(uint32_t bar, uint32_t count) {
  asm volatile("mbarrier.init.shared::cta.b64 [%0], %1;" :: "r"(bar), "r"(count) : "memory");
}
__device__ __forceinline__ void mbar_expect_tx(uint32_t bar, uint32_t bytes) {
  asm volatile("mbarrier.arrive.expect_tx.shared::cta.b64 _, [%0], %1;" :: "r"(bar), "r"(bytes) : "memory");
}
__device__ __forceinline__ void mbar_arrive_both(uint32_t bar, uint32_t peer) {
  asm volatile("{\n.reg .b32 r1;\n"
               "mapa.shared::cluster.u32 r1, %1, %2;\n"
               "mbarrier.arrive.shared::cta.b64 _, [%0];\n"
               "mbarrier.arrive.shared::cluster.b64 _, [r1];\n}"
               :: "r"(bar), "r"(bar + 8 * NSLOT), "r"(peer) : "memory");
}
__device__ __forceinline__ void mbar_wait(uint32_t bar, uint32_t parity) {
  asm volatile("{\n.reg .pred P1;\n.reg .u32 cnt;\nmov.u32 cnt, 0;\n"
               "LAB_WAIT:\n"
               "mbarrier.try_wait.parity.shared::cta.b64 P1, [%0], %1;\n"
               "@P1 bra DONE;\n"
               "add.u32 cnt, cnt, 1;\n"
               "setp.lt.u32 P1, cnt, 16777216;\n"
               "@P1 bra LAB_WAIT;\n"
               "trap;\n"
               "DONE:\n}"
               :: "r"(bar), "r"(parity) : "memory");
}
__device__ __forceinline__ uint64_t policy_evict_first() {
  uint64_t p; asm volatile("createpolicy.fractional.L2::evict_first.b64 %0, 1.0;" : "=l"(p)); return p;
}
__device__ __forceinline__ void tma_2d_nohint(uint32_t dst, const CUtensorMap* m, uint32_t bar, int c0, int c1) {
  asm volatile("cp.async.bulk.tensor.2d.shared::cluster.global.mbarrier::complete_tx::bytes [%0], [%1, {%3, %4}], [%2];"
               :: "r"(dst), "l"(m), "r"(bar), "r"(c0), "r"(c1) : "memory");
}
__device__ __forceinline__ void tma_2d_mc(uint32_t dst, const CUtensorMap* m, uint32_t bar, int c0, int c1) {
  asm volatile("cp.async.bulk.tensor.2d.shared::cluster.global.mbarrier::complete_tx::bytes.multicast::cluster [%0], [%1, {%3, %4}], [%2], %5;"
               :: "r"(dst), "l"(m), "r"(bar), "r"(c0), "r"(c1), "h"((uint16_t)3) : "memory");
}
__device__ __forceinline__ void tma_2d(uint32_t dst, const CUtensorMap* m, uint32_t bar, int c0, int c1, uint64_t pol) {
  asm volatile("cp.async.bulk.tensor.2d.shared::cluster.global.mbarrier::complete_tx::bytes.L2::cache_hint [%0], [%1, {%3, %4}], [%2], %5;"
               :: "r"(dst), "l"(m), "r"(bar), "r"(c0), "r"(c1), "l"(pol) : "memory");
}
__device__ __forceinline__ void tma_3d(uint32_t dst, const CUtensorMap* m, uint32_t bar, int c0, int c1, int c2, uint64_t pol) {
  asm volatile("cp.async.bulk.tensor.3d.shared::cluster.global.mbarrier::complete_tx::bytes.L2::cache_hint [%0], [%1, {%3, %4, %5}], [%2], %6;"
               :: "r"(dst), "l"(m), "r"(bar), "r"(c0), "r"(c1), "r"(c2), "l"(pol) : "memory");
}
__device__ __forceinline__ void tma_store_2d(const CUtensorMap* m, uint32_t src, int c0, int c1) {
  asm volatile("cp.async.bulk.tensor.2d.global.shared::cta.bulk_group [%0, {%2, %3}], [%1];"
               :: "l"(m), "r"(src), "r"(c0), "r"(c1) : "memory");
}
__device__ __forceinline__ bool mbar_test(uint32_t bar, uint32_t parity) {
  uint32_t ok;
  asm volatile("{\n.reg .pred p;\nmbarrier.test_wait.parity.shared::cta.b64 p, [%1], %2;\nselp.u32 %0, 1, 0, p;\n}"
               : "=r"(ok) : "r"(bar), "r"(parity) : "memory");
  return ok;
}
__device__ __forceinline__ int lane_id() { int l; asm volatile("mov.u32 %0, %%laneid;" : "=r"(l)); return l; }
__device__ __forceinline__ void mbar_arrive(uint32_t bar) {
  asm volatile("mbarrier.arrive.shared::cta.b64 _, [%0];" :: "r"(bar) : "memory");
}
__device__ __forceinline__ void wg_fence()  { asm volatile("wgmma.fence.sync.aligned;" ::: "memory"); }
__device__ __forceinline__ void wg_commit() { asm volatile("wgmma.commit_group.sync.aligned;" ::: "memory"); }
template <int N> __device__ __forceinline__ void wg_wait() { asm volatile("wgmma.wait_group.sync.aligned %0;" :: "n"(N) : "memory"); }
__device__ __forceinline__ void tok_wait(int id) { asm volatile("bar.sync %0, 256;" :: "r"(id) : "memory"); }
__device__ __forceinline__ void tok_pass(int id) { asm volatile("bar.arrive %0, 256;" :: "r"(id) : "memory"); }
__device__ __forceinline__ void cluster_arrive_relaxed() { asm volatile("barrier.cluster.arrive.relaxed.aligned;" ::: "memory"); }
__device__ __forceinline__ void cluster_wait()           { asm volatile("barrier.cluster.wait.aligned;" ::: "memory"); }
__device__ __forceinline__ unsigned ld_relaxed(const unsigned* p) {
  unsigned v; asm volatile("ld.relaxed.gpu.global.u32 %0, [%1];" : "=r"(v) : "l"(p) : "memory"); return v;
}
__device__ __forceinline__ unsigned ld_acquire(const unsigned* p) {
  unsigned v; asm volatile("ld.acquire.gpu.global.u32 %0, [%1];" : "=r"(v) : "l"(p) : "memory"); return v;
}
__device__ __forceinline__ void red_release_add(unsigned* p, unsigned v) {
  asm volatile("red.release.gpu.global.add.u32 [%0], %1;" :: "l"(p), "r"(v) : "memory");
}
__device__ __forceinline__ void spin_until(const unsigned* p, unsigned target) {
  asm volatile("{\n.reg .pred P1;\n.reg .u32 cnt, v;\nmov.u32 cnt, 0;\n"
               "LAB_SPIN:\n"
               "ld.acquire.gpu.global.u32 v, [%0];\n"
               "sub.u32 v, v, %1;\n"
               "setp.ge.s32 P1, v, 0;\n"
               "@P1 bra DONE;\n"
               "nanosleep.u32 20;\n"
               "add.u32 cnt, cnt, 1;\n"
               "setp.lt.u32 P1, cnt, 4194304;\n"
               "@P1 bra LAB_SPIN;\n"
               "trap;\n"
               "DONE:\n}"
               :: "l"(p), "r"(target) : "memory");
}
__device__ __forceinline__ uint32_t desc_lo(uint32_t addr, uint32_t lbo) { return ((addr & 0x3FFFF) >> 4) | ((lbo >> 4) << 16); }
__device__ __forceinline__ uint64_t desc(uint32_t lo, uint32_t byte_off = 0, uint32_t hi = 0x40000040u) {
  uint64_t d;
  asm("mov.b64 %0, {%1, %2};" : "=l"(d) : "r"(lo + (byte_off >> 4)), "r"(hi));
  return d;
}
__device__ __forceinline__ uint32_t pack_bf16(float lo, float hi) {
  uint32_t r; asm("cvt.rn.bf16x2.f32 %0, %1, %2;" : "=r"(r) : "f"(hi), "f"(lo)); return r;
}
__device__ __forceinline__ float ex2(float x) { float r; asm("ex2.approx.ftz.f32 %0, %1;" : "=f"(r) : "f"(x)); return r; }

__device__ __forceinline__ void wgmma_ss_n192_tb1(float (&d)[96], uint64_t descA, uint64_t descB) {
  asm volatile("{\n.reg .pred p;\n"
    "setp.ne.b32 p, 1, 0;\n"
    "wgmma.mma_async.sync.aligned.m64n192k16.f32.bf16.bf16 "
    "{%0, %1, %2, %3, %4, %5, %6, %7, %8, %9, %10, %11, %12, %13, %14, %15, "
    "%16, %17, %18, %19, %20, %21, %22, %23, %24, %25, %26, %27, %28, %29, %30, %31, "
    "%32, %33, %34, %35, %36, %37, %38, %39, %40, %41, %42, %43, %44, %45, %46, %47, "
    "%48, %49, %50, %51, %52, %53, %54, %55, %56, %57, %58, %59, %60, %61, %62, %63, "
    "%64, %65, %66, %67, %68, %69, %70, %71, %72, %73, %74, %75, %76, %77, %78, %79, "
    "%80, %81, %82, %83, %84, %85, %86, %87, %88, %89, %90, %91, %92, %93, %94, %95}, "
    "%96, %97, p, 1, 1, 0, 1;\n}\n"
    : "+f"(d[0]), "+f"(d[1]), "+f"(d[2]), "+f"(d[3]), "+f"(d[4]), "+f"(d[5]), "+f"(d[6]), "+f"(d[7]),
      "+f"(d[8]), "+f"(d[9]), "+f"(d[10]), "+f"(d[11]), "+f"(d[12]), "+f"(d[13]), "+f"(d[14]), "+f"(d[15]),
      "+f"(d[16]), "+f"(d[17]), "+f"(d[18]), "+f"(d[19]), "+f"(d[20]), "+f"(d[21]), "+f"(d[22]), "+f"(d[23]),
      "+f"(d[24]), "+f"(d[25]), "+f"(d[26]), "+f"(d[27]), "+f"(d[28]), "+f"(d[29]), "+f"(d[30]), "+f"(d[31]),
      "+f"(d[32]), "+f"(d[33]), "+f"(d[34]), "+f"(d[35]), "+f"(d[36]), "+f"(d[37]), "+f"(d[38]), "+f"(d[39]),
      "+f"(d[40]), "+f"(d[41]), "+f"(d[42]), "+f"(d[43]), "+f"(d[44]), "+f"(d[45]), "+f"(d[46]), "+f"(d[47]),
      "+f"(d[48]), "+f"(d[49]), "+f"(d[50]), "+f"(d[51]), "+f"(d[52]), "+f"(d[53]), "+f"(d[54]), "+f"(d[55]),
      "+f"(d[56]), "+f"(d[57]), "+f"(d[58]), "+f"(d[59]), "+f"(d[60]), "+f"(d[61]), "+f"(d[62]), "+f"(d[63]),
      "+f"(d[64]), "+f"(d[65]), "+f"(d[66]), "+f"(d[67]), "+f"(d[68]), "+f"(d[69]), "+f"(d[70]), "+f"(d[71]),
      "+f"(d[72]), "+f"(d[73]), "+f"(d[74]), "+f"(d[75]), "+f"(d[76]), "+f"(d[77]), "+f"(d[78]), "+f"(d[79]),
      "+f"(d[80]), "+f"(d[81]), "+f"(d[82]), "+f"(d[83]), "+f"(d[84]), "+f"(d[85]), "+f"(d[86]), "+f"(d[87]),
      "+f"(d[88]), "+f"(d[89]), "+f"(d[90]), "+f"(d[91]), "+f"(d[92]), "+f"(d[93]), "+f"(d[94]), "+f"(d[95])
    : "l"(descA), "l"(descB));
}

__device__ __forceinline__ void wgmma_ss_n192_tb1_init(float (&d)[96], uint64_t descA, uint64_t descB) {
  asm volatile("{\n.reg .pred p;\n"
    "setp.ne.b32 p, 0, 0;\n"
    "wgmma.mma_async.sync.aligned.m64n192k16.f32.bf16.bf16 "
    "{%0, %1, %2, %3, %4, %5, %6, %7, %8, %9, %10, %11, %12, %13, %14, %15, "
    "%16, %17, %18, %19, %20, %21, %22, %23, %24, %25, %26, %27, %28, %29, %30, %31, "
    "%32, %33, %34, %35, %36, %37, %38, %39, %40, %41, %42, %43, %44, %45, %46, %47, "
    "%48, %49, %50, %51, %52, %53, %54, %55, %56, %57, %58, %59, %60, %61, %62, %63, "
    "%64, %65, %66, %67, %68, %69, %70, %71, %72, %73, %74, %75, %76, %77, %78, %79, "
    "%80, %81, %82, %83, %84, %85, %86, %87, %88, %89, %90, %91, %92, %93, %94, %95}, "
    "%96, %97, p, 1, 1, 0, 1;\n}\n"
    : "=f"(d[0]), "=f"(d[1]), "=f"(d[2]), "=f"(d[3]), "=f"(d[4]), "=f"(d[5]), "=f"(d[6]), "=f"(d[7]),
      "=f"(d[8]), "=f"(d[9]), "=f"(d[10]), "=f"(d[11]), "=f"(d[12]), "=f"(d[13]), "=f"(d[14]), "=f"(d[15]),
      "=f"(d[16]), "=f"(d[17]), "=f"(d[18]), "=f"(d[19]), "=f"(d[20]), "=f"(d[21]), "=f"(d[22]), "=f"(d[23]),
      "=f"(d[24]), "=f"(d[25]), "=f"(d[26]), "=f"(d[27]), "=f"(d[28]), "=f"(d[29]), "=f"(d[30]), "=f"(d[31]),
      "=f"(d[32]), "=f"(d[33]), "=f"(d[34]), "=f"(d[35]), "=f"(d[36]), "=f"(d[37]), "=f"(d[38]), "=f"(d[39]),
      "=f"(d[40]), "=f"(d[41]), "=f"(d[42]), "=f"(d[43]), "=f"(d[44]), "=f"(d[45]), "=f"(d[46]), "=f"(d[47]),
      "=f"(d[48]), "=f"(d[49]), "=f"(d[50]), "=f"(d[51]), "=f"(d[52]), "=f"(d[53]), "=f"(d[54]), "=f"(d[55]),
      "=f"(d[56]), "=f"(d[57]), "=f"(d[58]), "=f"(d[59]), "=f"(d[60]), "=f"(d[61]), "=f"(d[62]), "=f"(d[63]),
      "=f"(d[64]), "=f"(d[65]), "=f"(d[66]), "=f"(d[67]), "=f"(d[68]), "=f"(d[69]), "=f"(d[70]), "=f"(d[71]),
      "=f"(d[72]), "=f"(d[73]), "=f"(d[74]), "=f"(d[75]), "=f"(d[76]), "=f"(d[77]), "=f"(d[78]), "=f"(d[79]),
      "=f"(d[80]), "=f"(d[81]), "=f"(d[82]), "=f"(d[83]), "=f"(d[84]), "=f"(d[85]), "=f"(d[86]), "=f"(d[87]),
      "=f"(d[88]), "=f"(d[89]), "=f"(d[90]), "=f"(d[91]), "=f"(d[92]), "=f"(d[93]), "=f"(d[94]), "=f"(d[95])
    : "l"(descA), "l"(descB));
}

__device__ __forceinline__ void wgmma_ss_n160_tb1(float (&d)[80], uint64_t descA, uint64_t descB) {
  asm volatile("{\n.reg .pred p;\n"
    "setp.ne.b32 p, 1, 0;\n"
    "wgmma.mma_async.sync.aligned.m64n160k16.f32.bf16.bf16 "
    "{%0, %1, %2, %3, %4, %5, %6, %7, %8, %9, %10, %11, %12, %13, %14, %15, "
    "%16, %17, %18, %19, %20, %21, %22, %23, %24, %25, %26, %27, %28, %29, %30, %31, "
    "%32, %33, %34, %35, %36, %37, %38, %39, %40, %41, %42, %43, %44, %45, %46, %47, "
    "%48, %49, %50, %51, %52, %53, %54, %55, %56, %57, %58, %59, %60, %61, %62, %63, "
    "%64, %65, %66, %67, %68, %69, %70, %71, %72, %73, %74, %75, %76, %77, %78, %79}, "
    "%80, %81, p, 1, 1, 0, 1;\n}\n"
    : "+f"(d[0]), "+f"(d[1]), "+f"(d[2]), "+f"(d[3]), "+f"(d[4]), "+f"(d[5]), "+f"(d[6]), "+f"(d[7]),
      "+f"(d[8]), "+f"(d[9]), "+f"(d[10]), "+f"(d[11]), "+f"(d[12]), "+f"(d[13]), "+f"(d[14]), "+f"(d[15]),
      "+f"(d[16]), "+f"(d[17]), "+f"(d[18]), "+f"(d[19]), "+f"(d[20]), "+f"(d[21]), "+f"(d[22]), "+f"(d[23]),
      "+f"(d[24]), "+f"(d[25]), "+f"(d[26]), "+f"(d[27]), "+f"(d[28]), "+f"(d[29]), "+f"(d[30]), "+f"(d[31]),
      "+f"(d[32]), "+f"(d[33]), "+f"(d[34]), "+f"(d[35]), "+f"(d[36]), "+f"(d[37]), "+f"(d[38]), "+f"(d[39]),
      "+f"(d[40]), "+f"(d[41]), "+f"(d[42]), "+f"(d[43]), "+f"(d[44]), "+f"(d[45]), "+f"(d[46]), "+f"(d[47]),
      "+f"(d[48]), "+f"(d[49]), "+f"(d[50]), "+f"(d[51]), "+f"(d[52]), "+f"(d[53]), "+f"(d[54]), "+f"(d[55]),
      "+f"(d[56]), "+f"(d[57]), "+f"(d[58]), "+f"(d[59]), "+f"(d[60]), "+f"(d[61]), "+f"(d[62]), "+f"(d[63]),
      "+f"(d[64]), "+f"(d[65]), "+f"(d[66]), "+f"(d[67]), "+f"(d[68]), "+f"(d[69]), "+f"(d[70]), "+f"(d[71]),
      "+f"(d[72]), "+f"(d[73]), "+f"(d[74]), "+f"(d[75]), "+f"(d[76]), "+f"(d[77]), "+f"(d[78]), "+f"(d[79])
    : "l"(descA), "l"(descB));
}

__device__ __forceinline__ void wgmma_ss_n160_tb1_init(float (&d)[80], uint64_t descA, uint64_t descB) {
  asm volatile("{\n.reg .pred p;\n"
    "setp.ne.b32 p, 0, 0;\n"
    "wgmma.mma_async.sync.aligned.m64n160k16.f32.bf16.bf16 "
    "{%0, %1, %2, %3, %4, %5, %6, %7, %8, %9, %10, %11, %12, %13, %14, %15, "
    "%16, %17, %18, %19, %20, %21, %22, %23, %24, %25, %26, %27, %28, %29, %30, %31, "
    "%32, %33, %34, %35, %36, %37, %38, %39, %40, %41, %42, %43, %44, %45, %46, %47, "
    "%48, %49, %50, %51, %52, %53, %54, %55, %56, %57, %58, %59, %60, %61, %62, %63, "
    "%64, %65, %66, %67, %68, %69, %70, %71, %72, %73, %74, %75, %76, %77, %78, %79}, "
    "%80, %81, p, 1, 1, 0, 1;\n}\n"
    : "=f"(d[0]), "=f"(d[1]), "=f"(d[2]), "=f"(d[3]), "=f"(d[4]), "=f"(d[5]), "=f"(d[6]), "=f"(d[7]),
      "=f"(d[8]), "=f"(d[9]), "=f"(d[10]), "=f"(d[11]), "=f"(d[12]), "=f"(d[13]), "=f"(d[14]), "=f"(d[15]),
      "=f"(d[16]), "=f"(d[17]), "=f"(d[18]), "=f"(d[19]), "=f"(d[20]), "=f"(d[21]), "=f"(d[22]), "=f"(d[23]),
      "=f"(d[24]), "=f"(d[25]), "=f"(d[26]), "=f"(d[27]), "=f"(d[28]), "=f"(d[29]), "=f"(d[30]), "=f"(d[31]),
      "=f"(d[32]), "=f"(d[33]), "=f"(d[34]), "=f"(d[35]), "=f"(d[36]), "=f"(d[37]), "=f"(d[38]), "=f"(d[39]),
      "=f"(d[40]), "=f"(d[41]), "=f"(d[42]), "=f"(d[43]), "=f"(d[44]), "=f"(d[45]), "=f"(d[46]), "=f"(d[47]),
      "=f"(d[48]), "=f"(d[49]), "=f"(d[50]), "=f"(d[51]), "=f"(d[52]), "=f"(d[53]), "=f"(d[54]), "=f"(d[55]),
      "=f"(d[56]), "=f"(d[57]), "=f"(d[58]), "=f"(d[59]), "=f"(d[60]), "=f"(d[61]), "=f"(d[62]), "=f"(d[63]),
      "=f"(d[64]), "=f"(d[65]), "=f"(d[66]), "=f"(d[67]), "=f"(d[68]), "=f"(d[69]), "=f"(d[70]), "=f"(d[71]),
      "=f"(d[72]), "=f"(d[73]), "=f"(d[74]), "=f"(d[75]), "=f"(d[76]), "=f"(d[77]), "=f"(d[78]), "=f"(d[79])
    : "l"(descA), "l"(descB));
}

__device__ __forceinline__ void wgmma_rs_n96_tb0(float (&d)[48], uint32_t a0, uint32_t a1, uint32_t a2, uint32_t a3, uint64_t descB) {
  asm volatile("{\n.reg .pred p;\n"
    "setp.ne.b32 p, 1, 0;\n"
    "wgmma.mma_async.sync.aligned.m64n96k16.f32.bf16.bf16 "
    "{%0, %1, %2, %3, %4, %5, %6, %7, %8, %9, %10, %11, %12, %13, %14, %15, "
    "%16, %17, %18, %19, %20, %21, %22, %23, %24, %25, %26, %27, %28, %29, %30, %31, "
    "%32, %33, %34, %35, %36, %37, %38, %39, %40, %41, %42, %43, %44, %45, %46, %47}, "
    "{%48, %49, %50, %51}, %52, p, 1, 1, 0;\n}\n"
    : "+f"(d[0]), "+f"(d[1]), "+f"(d[2]), "+f"(d[3]), "+f"(d[4]), "+f"(d[5]), "+f"(d[6]), "+f"(d[7]),
      "+f"(d[8]), "+f"(d[9]), "+f"(d[10]), "+f"(d[11]), "+f"(d[12]), "+f"(d[13]), "+f"(d[14]), "+f"(d[15]),
      "+f"(d[16]), "+f"(d[17]), "+f"(d[18]), "+f"(d[19]), "+f"(d[20]), "+f"(d[21]), "+f"(d[22]), "+f"(d[23]),
      "+f"(d[24]), "+f"(d[25]), "+f"(d[26]), "+f"(d[27]), "+f"(d[28]), "+f"(d[29]), "+f"(d[30]), "+f"(d[31]),
      "+f"(d[32]), "+f"(d[33]), "+f"(d[34]), "+f"(d[35]), "+f"(d[36]), "+f"(d[37]), "+f"(d[38]), "+f"(d[39]),
      "+f"(d[40]), "+f"(d[41]), "+f"(d[42]), "+f"(d[43]), "+f"(d[44]), "+f"(d[45]), "+f"(d[46]), "+f"(d[47])
    : "r"(a0), "r"(a1), "r"(a2), "r"(a3), "l"(descB));
}

__device__ __forceinline__ void wgmma_rs_n96_tb0_init(float (&d)[48], uint32_t a0, uint32_t a1, uint32_t a2, uint32_t a3, uint64_t descB) {
  asm volatile("{\n.reg .pred p;\n"
    "setp.ne.b32 p, 0, 0;\n"
    "wgmma.mma_async.sync.aligned.m64n96k16.f32.bf16.bf16 "
    "{%0, %1, %2, %3, %4, %5, %6, %7, %8, %9, %10, %11, %12, %13, %14, %15, "
    "%16, %17, %18, %19, %20, %21, %22, %23, %24, %25, %26, %27, %28, %29, %30, %31, "
    "%32, %33, %34, %35, %36, %37, %38, %39, %40, %41, %42, %43, %44, %45, %46, %47}, "
    "{%48, %49, %50, %51}, %52, p, 1, 1, 0;\n}\n"
    : "=f"(d[0]), "=f"(d[1]), "=f"(d[2]), "=f"(d[3]), "=f"(d[4]), "=f"(d[5]), "=f"(d[6]), "=f"(d[7]),
      "=f"(d[8]), "=f"(d[9]), "=f"(d[10]), "=f"(d[11]), "=f"(d[12]), "=f"(d[13]), "=f"(d[14]), "=f"(d[15]),
      "=f"(d[16]), "=f"(d[17]), "=f"(d[18]), "=f"(d[19]), "=f"(d[20]), "=f"(d[21]), "=f"(d[22]), "=f"(d[23]),
      "=f"(d[24]), "=f"(d[25]), "=f"(d[26]), "=f"(d[27]), "=f"(d[28]), "=f"(d[29]), "=f"(d[30]), "=f"(d[31]),
      "=f"(d[32]), "=f"(d[33]), "=f"(d[34]), "=f"(d[35]), "=f"(d[36]), "=f"(d[37]), "=f"(d[38]), "=f"(d[39]),
      "=f"(d[40]), "=f"(d[41]), "=f"(d[42]), "=f"(d[43]), "=f"(d[44]), "=f"(d[45]), "=f"(d[46]), "=f"(d[47])
    : "r"(a0), "r"(a1), "r"(a2), "r"(a3), "l"(descB));
}

__device__ __forceinline__ void wgmma_rs_n128_tb1(float (&d)[64], uint32_t a0, uint32_t a1, uint32_t a2, uint32_t a3, uint64_t descB) {
  asm volatile("{\n.reg .pred p;\n"
    "setp.ne.b32 p, 1, 0;\n"
    "wgmma.mma_async.sync.aligned.m64n128k16.f32.bf16.bf16 "
    "{%0, %1, %2, %3, %4, %5, %6, %7, %8, %9, %10, %11, %12, %13, %14, %15, "
    "%16, %17, %18, %19, %20, %21, %22, %23, %24, %25, %26, %27, %28, %29, %30, %31, "
    "%32, %33, %34, %35, %36, %37, %38, %39, %40, %41, %42, %43, %44, %45, %46, %47, "
    "%48, %49, %50, %51, %52, %53, %54, %55, %56, %57, %58, %59, %60, %61, %62, %63}, "
    "{%64, %65, %66, %67}, %68, p, 1, 1, 1;\n}\n"
    : "+f"(d[0]), "+f"(d[1]), "+f"(d[2]), "+f"(d[3]), "+f"(d[4]), "+f"(d[5]), "+f"(d[6]), "+f"(d[7]),
      "+f"(d[8]), "+f"(d[9]), "+f"(d[10]), "+f"(d[11]), "+f"(d[12]), "+f"(d[13]), "+f"(d[14]), "+f"(d[15]),
      "+f"(d[16]), "+f"(d[17]), "+f"(d[18]), "+f"(d[19]), "+f"(d[20]), "+f"(d[21]), "+f"(d[22]), "+f"(d[23]),
      "+f"(d[24]), "+f"(d[25]), "+f"(d[26]), "+f"(d[27]), "+f"(d[28]), "+f"(d[29]), "+f"(d[30]), "+f"(d[31]),
      "+f"(d[32]), "+f"(d[33]), "+f"(d[34]), "+f"(d[35]), "+f"(d[36]), "+f"(d[37]), "+f"(d[38]), "+f"(d[39]),
      "+f"(d[40]), "+f"(d[41]), "+f"(d[42]), "+f"(d[43]), "+f"(d[44]), "+f"(d[45]), "+f"(d[46]), "+f"(d[47]),
      "+f"(d[48]), "+f"(d[49]), "+f"(d[50]), "+f"(d[51]), "+f"(d[52]), "+f"(d[53]), "+f"(d[54]), "+f"(d[55]),
      "+f"(d[56]), "+f"(d[57]), "+f"(d[58]), "+f"(d[59]), "+f"(d[60]), "+f"(d[61]), "+f"(d[62]), "+f"(d[63])
    : "r"(a0), "r"(a1), "r"(a2), "r"(a3), "l"(descB));
}

__device__ __forceinline__ void wgmma_rs_n128_tb1_init(float (&d)[64], uint32_t a0, uint32_t a1, uint32_t a2, uint32_t a3, uint64_t descB) {
  asm volatile("{\n.reg .pred p;\n"
    "setp.ne.b32 p, 0, 0;\n"
    "wgmma.mma_async.sync.aligned.m64n128k16.f32.bf16.bf16 "
    "{%0, %1, %2, %3, %4, %5, %6, %7, %8, %9, %10, %11, %12, %13, %14, %15, "
    "%16, %17, %18, %19, %20, %21, %22, %23, %24, %25, %26, %27, %28, %29, %30, %31, "
    "%32, %33, %34, %35, %36, %37, %38, %39, %40, %41, %42, %43, %44, %45, %46, %47, "
    "%48, %49, %50, %51, %52, %53, %54, %55, %56, %57, %58, %59, %60, %61, %62, %63}, "
    "{%64, %65, %66, %67}, %68, p, 1, 1, 1;\n}\n"
    : "=f"(d[0]), "=f"(d[1]), "=f"(d[2]), "=f"(d[3]), "=f"(d[4]), "=f"(d[5]), "=f"(d[6]), "=f"(d[7]),
      "=f"(d[8]), "=f"(d[9]), "=f"(d[10]), "=f"(d[11]), "=f"(d[12]), "=f"(d[13]), "=f"(d[14]), "=f"(d[15]),
      "=f"(d[16]), "=f"(d[17]), "=f"(d[18]), "=f"(d[19]), "=f"(d[20]), "=f"(d[21]), "=f"(d[22]), "=f"(d[23]),
      "=f"(d[24]), "=f"(d[25]), "=f"(d[26]), "=f"(d[27]), "=f"(d[28]), "=f"(d[29]), "=f"(d[30]), "=f"(d[31]),
      "=f"(d[32]), "=f"(d[33]), "=f"(d[34]), "=f"(d[35]), "=f"(d[36]), "=f"(d[37]), "=f"(d[38]), "=f"(d[39]),
      "=f"(d[40]), "=f"(d[41]), "=f"(d[42]), "=f"(d[43]), "=f"(d[44]), "=f"(d[45]), "=f"(d[46]), "=f"(d[47]),
      "=f"(d[48]), "=f"(d[49]), "=f"(d[50]), "=f"(d[51]), "=f"(d[52]), "=f"(d[53]), "=f"(d[54]), "=f"(d[55]),
      "=f"(d[56]), "=f"(d[57]), "=f"(d[58]), "=f"(d[59]), "=f"(d[60]), "=f"(d[61]), "=f"(d[62]), "=f"(d[63])
    : "r"(a0), "r"(a1), "r"(a2), "r"(a3), "l"(descB));
}

__device__ __forceinline__ void wgmma_rs_n64_tb1(float (&d)[32], uint32_t a0, uint32_t a1, uint32_t a2, uint32_t a3, uint64_t descB) {
  asm volatile("{\n.reg .pred p;\n"
    "setp.ne.b32 p, 1, 0;\n"
    "wgmma.mma_async.sync.aligned.m64n64k16.f32.bf16.bf16 "
    "{%0, %1, %2, %3, %4, %5, %6, %7, %8, %9, %10, %11, %12, %13, %14, %15, "
    "%16, %17, %18, %19, %20, %21, %22, %23, %24, %25, %26, %27, %28, %29, %30, %31}, "
    "{%32, %33, %34, %35}, %36, p, 1, 1, 1;\n}\n"
    : "+f"(d[0]), "+f"(d[1]), "+f"(d[2]), "+f"(d[3]), "+f"(d[4]), "+f"(d[5]), "+f"(d[6]), "+f"(d[7]),
      "+f"(d[8]), "+f"(d[9]), "+f"(d[10]), "+f"(d[11]), "+f"(d[12]), "+f"(d[13]), "+f"(d[14]), "+f"(d[15]),
      "+f"(d[16]), "+f"(d[17]), "+f"(d[18]), "+f"(d[19]), "+f"(d[20]), "+f"(d[21]), "+f"(d[22]), "+f"(d[23]),
      "+f"(d[24]), "+f"(d[25]), "+f"(d[26]), "+f"(d[27]), "+f"(d[28]), "+f"(d[29]), "+f"(d[30]), "+f"(d[31])
    : "r"(a0), "r"(a1), "r"(a2), "r"(a3), "l"(descB));
}

__device__ __forceinline__ void wgmma_rs_n64_tb1_init(float (&d)[32], uint32_t a0, uint32_t a1, uint32_t a2, uint32_t a3, uint64_t descB) {
  asm volatile("{\n.reg .pred p;\n"
    "setp.ne.b32 p, 0, 0;\n"
    "wgmma.mma_async.sync.aligned.m64n64k16.f32.bf16.bf16 "
    "{%0, %1, %2, %3, %4, %5, %6, %7, %8, %9, %10, %11, %12, %13, %14, %15, "
    "%16, %17, %18, %19, %20, %21, %22, %23, %24, %25, %26, %27, %28, %29, %30, %31}, "
    "{%32, %33, %34, %35}, %36, p, 1, 1, 1;\n}\n"
    : "=f"(d[0]), "=f"(d[1]), "=f"(d[2]), "=f"(d[3]), "=f"(d[4]), "=f"(d[5]), "=f"(d[6]), "=f"(d[7]),
      "=f"(d[8]), "=f"(d[9]), "=f"(d[10]), "=f"(d[11]), "=f"(d[12]), "=f"(d[13]), "=f"(d[14]), "=f"(d[15]),
      "=f"(d[16]), "=f"(d[17]), "=f"(d[18]), "=f"(d[19]), "=f"(d[20]), "=f"(d[21]), "=f"(d[22]), "=f"(d[23]),
      "=f"(d[24]), "=f"(d[25]), "=f"(d[26]), "=f"(d[27]), "=f"(d[28]), "=f"(d[29]), "=f"(d[30]), "=f"(d[31])
    : "r"(a0), "r"(a1), "r"(a2), "r"(a3), "l"(descB));
}

template <int V> struct Int { static constexpr int value = V; };

struct Ring {
  uint32_t u;
  __device__ __forceinline__ uint32_t slot()  const { return u & (NSLOT - 1); }
  __device__ __forceinline__ uint32_t phase() const { return (u >> 2) & 1; }
  __device__ __forceinline__ uint32_t full(uint32_t full0)   const { return full0 + 8 * slot(); }
  __device__ __forceinline__ uint32_t empty(uint32_t full0)  const { return full0 + 8 * NSLOT + 8 * slot(); }
  __device__ __forceinline__ uint32_t addr(uint32_t ring)    const { return ring + slot() * SLOT_BYTES; }
  __device__ __forceinline__ Ring operator+(uint32_t d) const { return Ring{u + d}; }
};

__device__ __forceinline__ void softmax96(float (&s)[48], uint32_t (&p)[24], float& r0, float& r1) {
  const float c = 0.07216878364870322f * 1.4426950408889634f;
  float a0[6], a1[6];
#pragma unroll
  for (int j = 0; j < 6; j++) {
    a0[j] = fmaxf(fmaxf(s[8 * j], s[8 * j + 1]), fmaxf(s[8 * j + 4], s[8 * j + 5]));
    a1[j] = fmaxf(fmaxf(s[8 * j + 2], s[8 * j + 3]), fmaxf(s[8 * j + 6], s[8 * j + 7]));
  }
  float m0 = fmaxf(fmaxf(fmaxf(a0[0], a0[1]), fmaxf(a0[2], a0[3])), fmaxf(a0[4], a0[5]));
  float m1 = fmaxf(fmaxf(fmaxf(a1[0], a1[1]), fmaxf(a1[2], a1[3])), fmaxf(a1[4], a1[5]));
  m0 = fmaxf(m0, __shfl_xor_sync(0xffffffffu, m0, 1));
  m1 = fmaxf(m1, __shfl_xor_sync(0xffffffffu, m1, 1));
  m0 = fmaxf(m0, __shfl_xor_sync(0xffffffffu, m0, 2));
  m1 = fmaxf(m1, __shfl_xor_sync(0xffffffffu, m1, 2));
  const float b0 = -m0 * c, b1 = -m1 * c;
  float l0 = 0.f, l1 = 0.f;
#pragma unroll
  for (int j = 0; j < 12; j++) {
    const float e0 = ex2(fmaf(s[4 * j],     c, b0)), e1 = ex2(fmaf(s[4 * j + 1], c, b0));
    const float e2 = ex2(fmaf(s[4 * j + 2], c, b1)), e3 = ex2(fmaf(s[4 * j + 3], c, b1));
    l0 += e0 + e1;
    l1 += e2 + e3;
    p[2 * j]     = pack_bf16(e0, e1);
    p[2 * j + 1] = pack_bf16(e2, e3);
  }
  l0 += __shfl_xor_sync(0xffffffffu, l0, 1);
  l1 += __shfl_xor_sync(0xffffffffu, l1, 1);
  l0 += __shfl_xor_sync(0xffffffffu, l0, 2);
  l1 += __shfl_xor_sync(0xffffffffu, l1, 2);
  asm("rcp.approx.ftz.f32 %0, %1;" : "=f"(r0) : "f"(l0));
  asm("rcp.approx.ftz.f32 %0, %1;" : "=f"(r1) : "f"(l1));
}

template <bool INIT>
__device__ __forceinline__ void qk_mma(float (&s)[48], const uint32_t (&qf)[48], uint32_t box0, uint32_t box1, uint32_t box2, int pass_id) {
  const uint32_t d0 = desc_lo(box0, 16), d1 = desc_lo(box1, 16), d2 = desc_lo(box2, 16);
  if (INIT) wgmma_rs_n96_tb0_init(s, qf[0], qf[1], qf[2], qf[3], desc(d0));
  else      wgmma_rs_n96_tb0(s, qf[0], qf[1], qf[2], qf[3], desc(d0));
#pragma unroll
  for (int k = 1; k < 12; k++) {
    wgmma_rs_n96_tb0(s, qf[4 * k], qf[4 * k + 1], qf[4 * k + 2], qf[4 * k + 3], desc(k < 4 ? d0 : k < 8 ? d1 : d2, (k & 3) * 32));
  }
  tok_pass(pass_id);
}
template <bool INIT>
__device__ __forceinline__ void pv_mma(float (&o)[96], const uint32_t (&pf)[24], uint32_t box01, uint32_t box2, int pass_id) {
  float (&oa)[64] = *reinterpret_cast<float (*)[64]>(&o[0]);
  float (&ob)[32] = *reinterpret_cast<float (*)[32]>(&o[64]);
  const uint32_t da = desc_lo(box01, 12288), db = desc_lo(box2, 12288);
  if (INIT) { wgmma_rs_n128_tb1_init(oa, pf[0], pf[1], pf[2], pf[3], desc(da)); wgmma_rs_n64_tb1_init(ob, pf[0], pf[1], pf[2], pf[3], desc(db)); }
  else      { wgmma_rs_n128_tb1(oa, pf[0], pf[1], pf[2], pf[3], desc(da));      wgmma_rs_n64_tb1(ob, pf[0], pf[1], pf[2], pf[3], desc(db)); }
#pragma unroll
  for (int k = 1; k < 6; k++) {
    wgmma_rs_n128_tb1(oa, pf[4 * k], pf[4 * k + 1], pf[4 * k + 2], pf[4 * k + 3], desc(da, k * 2048));
    wgmma_rs_n64_tb1(ob, pf[4 * k], pf[4 * k + 1], pf[4 * k + 2], pf[4 * k + 3], desc(db, k * 2048));
  }
  tok_pass(pass_id);
}

__global__ void __cluster_dims__(2, 1, 1) __launch_bounds__(NTHREADS, 1)
fused_attn_kernel(const __grid_constant__ Params prm) {
  extern __shared__ uint8_t smem_raw[];
  __shared__ uint64_t s_bars[3 * NSLOT + 11];
  __shared__ uint32_t s_dummy[64];
  __shared__ volatile uint32_t s_prog;

  const uint32_t ring = (smem_u32(smem_raw) + 1023) & ~1023u;
  const uint32_t stg  = ring + NSLOT * SLOT_BYTES;
  const uint32_t full0 = smem_u32(&s_bars[0]);
  const uint32_t o_done  = full0 + 24 * NSLOT;
  const uint32_t x_free  = o_done + 80;
  const uint32_t o_ready = o_done + 48;

  const int tid = threadIdx.x, lane = tid & 31;
  const int warp = __shfl_sync(0xffffffffu, tid >> 5, 0);
  const int rank = blockIdx.x & 1, cl = logical_cluster(blockIdx.x >> 1), cta = 2 * cl + rank;
  const int grp = cl >> 3, prob = grp >> 2, bp = grp & 3, j8 = cl & 7;
  const int split = j8 >> 1;

  if (tid == 13 * 32) {
    asm volatile("prefetch.tensormap [%0];" :: "l"(&prm.wq[prob]) : "memory");
    asm volatile("prefetch.tensormap [%0];" :: "l"(&prm.x1[prob]) : "memory");
    asm volatile("prefetch.tensormap [%0];" :: "l"(&prm.x[prob]) : "memory");
  }
  if (tid == 12 * 32) {
#pragma unroll
    for (int s = 0; s < NSLOT; s++) { mbar_init(full0 + 8 * s, 1); mbar_init(full0 + 8 * NSLOT + 8 * s, 3); mbar_init(full0 + 16 * NSLOT + 8 * s, 3); }
    for (int s = 0; s < 6; s++) mbar_init(o_done + 8 * s, 12);
    for (int s = 0; s < 4; s++) mbar_init(o_ready + 8 * s, 1);
    mbar_init(x_free, 3);
    s_prog = NSLOT;
    asm volatile("fence.mbarrier_init.release.cluster;" ::: "memory");
  }
  __syncthreads();
  cluster_arrive_relaxed();
  if (tid == 12 * 32) {
    const int h = 2 * j8 + rank;
    const uint64_t pol = policy_evict_first();
#pragma unroll
    for (int s = 0; s < NSLOT; s++) {
      mbar_expect_tx(full0 + 8 * s, SLOT_BYTES);
      tma_2d_nohint(ring + s * SLOT_BYTES, &prm.x1[prob], full0 + 8 * s, 64 * s, 192 * bp);
      tma_3d(ring + s * SLOT_BYTES + B_OFF, &prm.wq[prob], full0 + 8 * s, 0, 64 * s, 3 * h, pol);
    }
  }
  __syncwarp();
  cluster_wait();

  if (warp >= 12) {
    asm volatile("setmaxnreg.dec.sync.aligned.u32 32;");
    if (warp == 12) {
      if (lane == 0) {
        Ring r{0};
        const uint64_t pol_s = policy_evict_first();
        const int ncol0 = 320 * (j8 & 1);
#pragma unroll 1
        for (int w = 0; w < 2; w++) {
          const int h = 16 * w + 2 * j8 + rank;
#pragma unroll 1
          for (int ks = 0; ks < 10; ks++) {
            const uint32_t fb = r.full(full0), sl = r.addr(ring);
            if (r.u >= NSLOT) {
              mbar_wait(r.empty(full0), r.phase() ^ 1);
              mbar_expect_tx(fb, SLOT_BYTES);
              s_prog = r.u;
              tma_3d(sl + B_OFF, &prm.wq[prob], fb, 0, 64 * ks, 3 * h, pol_s);
              mbar_wait(r.empty(full0) + 8 * NSLOT, r.phase() ^ 1);
              tma_2d_mc(sl + rank * 12288, &prm.x[prob], fb, 64 * ks, 192 * bp + 96 * rank);
            }
            r.u++;
          }
#pragma unroll 1
          for (int t = 0; t < 3; t++) {
            const uint32_t fb = r.full(full0), sl = r.addr(ring);
            const int row0 = ((2 * bp) * 32 + h) * 96, row1 = row0 + 32 * 96;
            mbar_wait(r.empty(full0), r.phase() ^ 1);
            mbar_expect_tx(fb, SLOT_BYTES);
            s_prog = r.u;
            if (t == 0) {
              tma_3d(sl,         &prm.k[prob],  fb, 0, row0, 0, pol_s);
              tma_3d(sl + 36864, &prm.k1[prob], fb, 0, row1, 0, pol_s);
            } else if (t == 1) {
              tma_3d(sl,         &prm.k1[prob], fb, 0, row1, 1, pol_s);
              tma_3d(sl + 12288, &prm.k1[prob], fb, 0, row1, 2, pol_s);
              tma_3d(sl + 24576, &prm.v1[prob], fb, 0, row0, 0, pol_s);
              tma_3d(sl + 36864, &prm.v1[prob], fb, 0, row0, 1, pol_s);
            } else {
              tma_3d(sl,         &prm.v1[prob], fb, 0, row0, 2, pol_s);
              tma_3d(sl + 12288, &prm.v[prob],  fb, 0, row1, 0, pol_s);
            }
            mbar_wait(r.empty(full0) + 8 * NSLOT, r.phase() ^ 1);
            r.u++;
          }
        }
#pragma unroll 1
        for (int i = 0; i < 24; i++) {
          const int h = i < 12 ? 4 * split + i / 3 : 16 + 4 * split + (i & 3);
          const int c = i < 12 ? i % 3 : (i - 12) >> 2;
          const uint32_t fb = r.full(full0), sl = r.addr(ring);
          const int k0 = h * 192 + c * 64;
          mbar_wait(r.empty(full0), r.phase() ^ 1);
          mbar_expect_tx(fb, SLOT_BYTES);
          s_prog = r.u;
          tma_2d(sl + B_OFF,         &prm.wo[prob],   fb, ncol0 + 192 * rank,      k0, pol_s);
          tma_2d(sl + B_OFF + 8192,  &prm.wo[prob],   fb, ncol0 + 192 * rank + 64, k0, pol_s);
          tma_2d(sl + B_OFF + 16384, &prm.wo[prob],   fb, ncol0 + 128, k0, pol_s);
          if (i == 0 || (i >= 12 && (i & 3) == 0)) {
            mbar_wait(o_ready + 8 * (i == 0 ? 0 : (i >> 2) - 2), 0);
          }
          mbar_wait(r.empty(full0) + 8 * NSLOT, r.phase() ^ 1);
          tma_2d_mc(sl + rank * 12288, &prm.o_ld, fb, k0, prob * 768 + 192 * bp + 96 * rank);
          r.u++;
        }
      }
    } else if (warp == 13) {
      {
        const unsigned obase = 3u * ld_relaxed(&prm.epoch[cta]);
        uint32_t pub = 0, wat = 0;
#pragma unroll 1
        for (int it = 0; it < (1 << 22) && (pub < 6 || wat < 4); it++) {
          if (pub < 6 && mbar_test(o_done + 8 * pub, 0)) {
            uint32_t n = 1;
            while ((pub + n) % 3 != 0 && mbar_test(o_done + 8 * (pub + n), 0)) n++;
            if (lane == 0) {
              red_release_add(&prm.ready[grp * 32 + 16 * (pub >= 3) + 2 * j8 + rank], n);
            }
            __syncwarp();
            pub += n;
          } else if (wat < 4 && pub > wat + 2) {
            const unsigned tgt = obase + (wat == 0 ? 3u : wat);
            const unsigned a = ld_acquire(&prm.ready[grp * 32 + (wat == 0 ? 0 : 16) + 4 * split + (lane & 3)]);
            if (__all_sync(0xffffffffu, (int)(a - tgt) >= 0)) {
              if (lane == 0) {
                asm volatile("fence.proxy.async;" ::: "memory");
                mbar_arrive(o_ready + 8 * wat);
              }
              __syncwarp();
              wat++;
            }
          } else {
            mbar_wait(o_done + 8 * pub, 0);
          }
        }
      }
    } else {
      const int h0 = 2 * j8 + rank;
      const uint8_t* wqp = prm.wqptr[prob];
      auto addr_of = [&](int n) -> const uint8_t* {
        if (n < 9 || (n >= 45 && n < 60)) {
          const bool second = n >= 45;
          const int i = (second ? n - 45 : n + 6) * 32 + lane;
          const int ks = i / 48, rem = i - ks * 48;
          return wqp + (size_t)(64 * ks + 16 * bp + rem / 3) * 12288 + (h0 + (second ? 16 : 0)) * 384 + (rem % 3) * 128;
        }
        const bool second = n >= 60;
        const int m = second ? n - 60 : n - 9, tile = m / 9;
        const uint8_t* base = (tile < 2) ? prm.kptr[prob] : prm.vptr[prob];
        return base + (size_t)((2 * bp + (tile & 1)) * 32 + h0 + (second ? 16 : 0)) * KV_BYTES + (m - 9 * tile) * 4096 + lane * 128;
      };
      auto use_of = [&](int n) -> int {
        if (n < 9)  return ((n + 6) * 32) / 48;
        if (n < 45) { const int t = (n - 9) / 9; return 10 + (t < 2 ? 0 : t - 1); }
        if (n < 60) return 13 + ((n - 45) * 32) / 48;
        const int t = (n - 60) / 9;
        return 23 + (t < 2 ? 0 : t - 1);
      };
      auto release_of = [&](int n) -> int {
        if (n < 9)  return 0;
        if (n < 45) return PF_R0 + ((n - 9) * (PF_R1 - PF_R0)) / 36;
        if (n < 60) return PF_R1 + ((n - 45) * (PF_R2 - PF_R1)) / 15;
        return PF_R2 + ((n - 60) * (PF_R3 - PF_R2)) / 36;
      };
      const uint32_t dummy = smem_u32(&s_dummy[tid & 63]);
#pragma unroll 1
      for (int n = warp - 14; n < 96; n += 2) {
        const int u = use_of(n), rel = release_of(n);
        int guard = 0;
        while ((int)s_prog < rel && ++guard < (1 << 20)) __nanosleep(100);
        if ((int)s_prog < u)
          asm volatile("cp.async.ca.shared.global.L2::128B [%0], [%1], 4;" :: "r"(dummy), "l"(addr_of(n)) : "memory");
        asm volatile("cp.async.commit_group;" ::: "memory");
        asm volatile("cp.async.wait_group %0;" :: "n"(PF_WIN) : "memory");
      }
      asm volatile("cp.async.wait_group 0;" ::: "memory");
    }
  } else {
    asm volatile("setmaxnreg.inc.sync.aligned.u32 160;");
    const int wg = warp >> 2, wq4 = warp & 3;
    const bool elected = wq4 == 0 && lane_id() == 0;
    const uint32_t descA0 = desc_lo(ring + wg * 8192, 16), descB0 = desc_lo(ring + B_OFF, 8192);
    Ring r{0};
    uint32_t pend[32];
    const uint32_t wstg = stg + warp * 2048;
    auto stg_acquire = [&]() {
      if (lane_id() == 0) asm volatile("cp.async.bulk.wait_group.read 0;" ::: "memory");
      __syncwarp();
    };
    auto stage_in = [&](const uint32_t* v) {
      stg_acquire();
      const int lane = lane_id(), r8 = lane & 7;
      const uint32_t st_base = wstg + (((lane >> 3) & 1) * 8 + r8) * 128;
#pragma unroll
      for (int jj = 0; jj < 4; jj++) {
        const uint32_t addr = st_base + (((2 * jj + (lane >> 4)) ^ r8) << 4);
        asm volatile("stmatrix.sync.aligned.m8n8.x4.shared.b16 [%0], {%1, %2, %3, %4};"
                     :: "r"(addr), "r"(v[4 * jj]), "r"(v[4 * jj + 1]), "r"(v[4 * jj + 2]), "r"(v[4 * jj + 3]) : "memory");
      }
    };
    auto send = [&](int wv, int box) {
      asm volatile("fence.proxy.async.shared::cta;" ::: "memory");
      __syncwarp();
      if (lane_id() == 0) {
        tma_store_2d(&prm.o_st, wstg, (16 * wv + 2 * j8 + rank) * 192 + 64 * box, prob * 768 + 192 * bp + 16 * warp);
        asm volatile("cp.async.bulk.commit_group;" ::: "memory");
      }
    };
    auto landed = [&](int ev, auto pending) {
      if (lane_id() == 0) {
        asm volatile("cp.async.bulk.wait_group %0;" :: "n"(decltype(pending)::value) : "memory");
        mbar_arrive(o_done + 8 * ev);
      }
    };

#pragma unroll 1
    for (int w = 0; w < 2; w++) {
      uint32_t qf[48];
      {
        float acc[96];
        {
          const uint32_t da = descA0 + r.slot() * (SLOT_BYTES >> 4), db = descB0 + r.slot() * (SLOT_BYTES >> 4);
          mbar_wait(r.full(full0), r.phase());
          if (w > 0) { if (wg == 0) tok_wait(14); else if (wg == 2) tok_wait(15); }
          wg_fence();
          wgmma_ss_n192_tb1_init(acc, desc(da), desc(db));
#pragma unroll
          for (int k = 1; k < 4; k++) wgmma_ss_n192_tb1(acc, desc(da, k * 32), desc(db, k * 2048));
          wg_commit();
          if (w > 0 && wg == 0) tok_pass(15);
          if (w > 0) send(0, 0);
          r.u++;
        }
#pragma unroll 1
        for (int ks = 1; ks < 8; ks++) {
          const uint32_t da = descA0 + r.slot() * (SLOT_BYTES >> 4), db = descB0 + r.slot() * (SLOT_BYTES >> 4);
          mbar_wait(r.full(full0), r.phase());
          wg_fence();
          wgmma_ss_n192_tb1(acc, desc(da), desc(db));
          wg_commit();
          wg_wait<1>();
          if (elected) mbar_arrive_both(Ring{r.u - 1}.empty(full0), rank ^ 1);
#pragma unroll
          for (int k = 1; k < 4; k++) wgmma_ss_n192_tb1(acc, desc(da, k * 32), desc(db, k * 2048));
          wg_commit();
          if (w > 0) {
            if (ks == FL_B1)      { stage_in(pend);      send(0, 1); }
            else if (ks == FL_B2) { stage_in(pend + 16); send(0, 2); }
            else if (ks == FL_LD) { landed(0, Int<0>{}); landed(1, Int<0>{}); landed(2, Int<0>{}); }
          }
          r.u++;
        }
        {
          const Ring r8 = r, r9 = r + 1;
          r.u += 2;
          wg_wait<0>();
          if (elected) mbar_arrive_both(Ring{r8.u - 1}.empty(full0), rank ^ 1);
          mbar_wait(r8.full(full0), r8.phase());
          mbar_wait(r9.full(full0), r9.phase());
          if (wg != 1) tok_wait(wg == 0 ? 4 : 5);
          const uint32_t da8 = descA0 + r8.slot() * (SLOT_BYTES >> 4), db8 = descB0 + r8.slot() * (SLOT_BYTES >> 4);
          const uint32_t da9 = descA0 + r9.slot() * (SLOT_BYTES >> 4), db9 = descB0 + r9.slot() * (SLOT_BYTES >> 4);
          wg_fence();
#pragma unroll
          for (int k = 0; k < 4; k++) wgmma_ss_n192_tb1(acc, desc(da8, k * 32), desc(db8, k * 2048));
          wg_commit();
#pragma unroll
          for (int k = 0; k < 4; k++) wgmma_ss_n192_tb1(acc, desc(da9, k * 32), desc(db9, k * 2048));
          wg_commit();
          if (wg != 2) tok_pass(wg == 1 ? 4 : 5);
          wg_wait<1>();
          if (elected) mbar_arrive_both(r8.empty(full0), rank ^ 1);
          mbar_wait(r.full(full0), r.phase());
          if (wg == 2) mbar_wait((r + 1).full(full0), (r + 1).phase());
          wg_wait<0>();
          if (elected) mbar_arrive_both(r9.empty(full0), rank ^ 1);
        }
        stg_acquire();
        const int lane = lane_id();
#pragma unroll
        for (int i = 0; i < 4; i++)
          asm volatile("st.shared.v4.u32 [%0], {%1, %2, %3, %4};"
                       :: "r"(wstg + i * 512 + lane * 16),
                          "r"(pack_bf16(acc[64 + 8 * i], acc[65 + 8 * i])), "r"(pack_bf16(acc[66 + 8 * i], acc[67 + 8 * i])),
                          "r"(pack_bf16(acc[68 + 8 * i], acc[69 + 8 * i])), "r"(pack_bf16(acc[70 + 8 * i], acc[71 + 8 * i])) : "memory");
#pragma unroll
        for (int i = 0; i < 32; i++) qf[i] = pack_bf16(acc[2 * i], acc[2 * i + 1]);
        asm volatile("" ::: "memory");
#pragma unroll
        for (int i = 0; i < 4; i++)
          asm volatile("ld.shared.v4.u32 {%0, %1, %2, %3}, [%4];"
                       : "=r"(qf[32 + 4 * i]), "=r"(qf[33 + 4 * i]), "=r"(qf[34 + 4 * i]), "=r"(qf[35 + 4 * i])
                       : "r"(wstg + i * 512 + lane * 16) : "memory");
      }
      const Ring rX = r, rY = r + 1, rZ = r + 2;
      r.u += 3;
      uint32_t pf[24];
      float rinv0, rinv1;
      bool z_ready;
      const uint32_t aX = rX.addr(ring), aY = rY.addr(ring), aZ = rZ.addr(ring);
      {
        float s[48];
        if (wg != 1) tok_wait(wg == 0 ? 7 : 9);
        wg_fence();
        qk_mma<true>(s, qf, wg == 2 ? aX + 36864 : aX, wg == 2 ? aY : aX + 12288, wg == 2 ? aY + 12288 : aX + 24576, wg == 1 ? 7 : wg == 0 ? 8 : 10);
        wg_commit();
        if (wg != 2) mbar_wait(rY.full(full0), rY.phase());
        wg_wait<0>();
        if (wg == 1) {
          if (wq4 < 2) {
#pragma unroll
            for (int i = 0; i < 48; i++) qf[i] = 0u;
          } else {
#pragma unroll
            for (int i = 0; i < 48; i++) s[i] = 0.f;
          }
          tok_wait(8);
          wg_fence();
          qk_mma<false>(s, qf, aX + 36864, aY, aY + 12288, 9);
          wg_commit();
          wg_wait<0>();
        }
        if (elected) { mbar_arrive_both(rX.empty(full0), rank ^ 1); if (wg == 2) mbar_arrive_both(rY.empty(full0), rank ^ 1); }
        __syncwarp();
        z_ready = mbar_test(rZ.full(full0), rZ.phase());
        softmax96(s, pf, rinv0, rinv1);
      }
      float o[96];
      {
        if (!__all_sync(0xffffffffu, z_ready)) mbar_wait(rZ.full(full0), rZ.phase());
        tok_wait(wg == 0 ? 10 : wg == 1 ? 11 : 12);
        wg_fence();
        pv_mma<true>(o, pf, wg == 2 ? aZ + 12288 : aY + 24576, wg == 2 ? aZ + 36864 : aZ, wg == 0 ? 11 : wg == 1 ? 12 : 13);
        wg_commit();
        wg_wait<0>();
        if (wg == 1) {
          if (elected) mbar_arrive_both(rY.empty(full0), rank ^ 1);
          if (wq4 < 2) {
#pragma unroll
            for (int i = 0; i < 24; i++) pf[i] = 0u;
          } else {
#pragma unroll
            for (int i = 0; i < 96; i++) o[i] = 0.f;
          }
          tok_wait(13);
          wg_fence();
          pv_mma<false>(o, pf, aZ + 12288, aZ + 36864, 14);
          wg_commit();
          wg_wait<0>();
        }
        if (elected) { if (wg == 0) mbar_arrive_both(rY.empty(full0), rank ^ 1); mbar_arrive_both(rZ.empty(full0), rank ^ 1); }
      }
      {
        uint32_t v[16];
#pragma unroll
        for (int i = 0; i < 16; i++) { const float ri = (i & 1) ? rinv1 : rinv0; v[i] = pack_bf16(o[2 * i] * ri, o[2 * i + 1] * ri); }
#pragma unroll
        for (int i = 0; i < 32; i++) { const float ri = (i & 1) ? rinv1 : rinv0; pend[i] = pack_bf16(o[32 + 2 * i] * ri, o[33 + 2 * i] * ri); }
        stage_in(v);
      }
    }

    const unsigned otarget = ld_relaxed(&prm.epoch[cta]) + 1u, target = 3u * otarget;
    const uint32_t bhi = 0x40000040u | (rank ? 4u << 17 : 0u);
    float acc[80];
    {
      {
        const uint32_t da = descA0 + r.slot() * (SLOT_BYTES >> 4), db = descB0 + r.slot() * (SLOT_BYTES >> 4);
        mbar_wait(r.full(full0), r.phase());
        if (wg == 0) tok_wait(14); else if (wg == 2) tok_wait(15);
        wg_fence();
        wgmma_ss_n160_tb1_init(acc, desc(da), desc(db, 0, bhi));
#pragma unroll
        for (int k = 1; k < 4; k++) wgmma_ss_n160_tb1(acc, desc(da, k * 32), desc(db, k * 2048, bhi));
        wg_commit();
        if (wg == 0) tok_pass(15);
        send(1, 0);
        r.u++;
      }
#pragma unroll 1
      for (int ks = 1; ks < 24 - TAIL_L; ks++) {
        const uint32_t da = descA0 + r.slot() * (SLOT_BYTES >> 4), db = descB0 + r.slot() * (SLOT_BYTES >> 4);
        mbar_wait(r.full(full0), r.phase());
        wg_fence();
        wgmma_ss_n160_tb1(acc, desc(da), desc(db, 0, bhi));
        wg_commit();
        wg_wait<1>();
        if (elected) mbar_arrive_both(Ring{r.u - 1}.empty(full0), rank ^ 1);
#pragma unroll
        for (int k = 1; k < 4; k++) wgmma_ss_n160_tb1(acc, desc(da, k * 32), desc(db, k * 2048, bhi));
        wg_commit();
        {
          if (ks == FL2_B1)      { landed(3, Int<0>{}); stage_in(pend);      send(1, 1); }
          else if (ks == FL2_B2) { landed(4, Int<0>{}); stage_in(pend + 16); send(1, 2); }
          else if (ks == FL2_LD) { landed(5, Int<0>{}); }
        }
        r.u++;
      }
      static_assert(TAIL_L == NSLOT - 1, "the slots of the last NSLOT ring uses are not released");
      if (wg > 0) {
        wg_wait<0>();
        if (elected) mbar_arrive(x_free);
#pragma unroll
        for (int i = 0; i < TAIL_L; i++) mbar_wait((r + i).full(full0), (r + i).phase());
        tok_wait(3 + wg);
      } else {
        mbar_wait(r.full(full0), r.phase());
        mbar_wait((r + 1).full(full0), (r + 1).phase());
      }
      wg_fence();
#pragma unroll
      for (int i = 0; i < TAIL_L; i++) {
        const uint32_t da = descA0 + (r + i).slot() * (SLOT_BYTES >> 4), db = descB0 + (r + i).slot() * (SLOT_BYTES >> 4);
        if (i == TAIL_L - 1 && wg == 0) mbar_wait((r + i).full(full0), (r + i).phase());
#pragma unroll
        for (int k = 0; k < 4; k++) wgmma_ss_n160_tb1(acc, desc(da, k * 32), desc(db, k * 2048, bhi));
      }
      wg_commit();
      if (wg < 2) tok_pass(4 + wg);
      wg_wait<0>();
      if (wg == 0 && elected) mbar_arrive(x_free);
    }
    {
      const int lane = lane_id(), t = warp * 32 + lane;
      const uint32_t xstg = Ring{r.u - 1}.addr(ring) + warp * 4096;
      mbar_wait(x_free, 0);
#pragma unroll
      for (int q = 0; q < 4; q++) {
        const int blk0 = q == 0 ? 0 : q == 1 ? 6 : q == 2 ? 10 : 16, npk = (q & 1) ? 2 : 3;
        const int cum = q == 0 ? 0 : q == 1 ? 3 : q == 2 ? 5 : 8;
        if (q != split) {
          const uint32_t dst = xstg + (cum - (split < q ? ((split & 1) ? 2 : 3) : 0)) * 512 + lane * 16;
#pragma unroll
          for (int i = 0; i < 3; i++) {
            if (i < npk) {
              const int a = 4 * blk0 + 8 * i;
              asm volatile("st.shared.v4.u32 [%0], {%1, %2, %3, %4};"
                           :: "r"(dst + i * 512), "r"(pack_bf16(acc[a], acc[a + 1])), "r"(pack_bf16(acc[a + 2], acc[a + 3])),
                              "r"(pack_bf16(acc[a + 4], acc[a + 5])), "r"(pack_bf16(acc[a + 6], acc[a + 7])) : "memory");
            }
          }
        }
      }
      asm volatile("fence.proxy.async.shared::cta;" ::: "memory");
      __syncwarp();
      if (lane == 0) {
#pragma unroll
        for (int q = 0; q < 4; q++) {
          const int npk = (q & 1) ? 2 : 3, cum = q == 0 ? 0 : q == 1 ? 3 : q == 2 ? 5 : 8;
          if (q != split) {
            const int dcta = (grp * 8 + 2 * q + (j8 & 1)) * 2 + rank;
            const int srcslot = split < q ? split : split - 1;
            asm volatile("cp.async.bulk.global.shared::cta.bulk_group [%0], [%1], %2;"
                         :: "l"(prm.part + ((size_t)(dcta * 3 + srcslot) * 12 + warp) * 96),
                            "r"(xstg + (cum - (split < q ? ((split & 1) ? 2 : 3) : 0)) * 512), "r"(npk * 512) : "memory");
          }
        }
        asm volatile("cp.async.bulk.commit_group;" ::: "memory");
        asm volatile("cp.async.bulk.wait_group 0;" ::: "memory");
        asm volatile("fence.acq_rel.gpu;" ::: "memory");
#pragma unroll
        for (int q = 0; q < 4; q++) {
          if (q != split)
            asm volatile("red.relaxed.gpu.global.add.u32 [%0], %1;"
                         :: "l"(&prm.xflag[((grp * 8 + 2 * q + (j8 & 1)) * 2 + rank) * 12 + warp]), "r"(1u) : "memory");
        }
      }
      __syncwarp();
      const int nown = (split & 1) ? 2 : 3;
      float own[24];
#pragma unroll
      for (int i = 0; i < 24; i++)
        own[i] = split == 0 ? acc[i] : split == 1 ? acc[24 + (i & 15)] : split == 2 ? acc[40 + i] : acc[64 + (i & 15)];
      spin_until(&prm.xflag[cta * 12 + warp], target);
      {
        const uint4* src = prm.part + ((size_t)(cta * 3) * 12 + warp) * 96 + lane;
        uint4 v[9];
#pragma unroll
        for (int sidx = 0; sidx < 3; sidx++) {
          v[3 * sidx]     = __ldcg(src + sidx * (12 * 96));
          v[3 * sidx + 1] = __ldcg(src + sidx * (12 * 96) + 32);
          v[3 * sidx + 2] = nown == 3 ? __ldcg(src + sidx * (12 * 96) + 64) : make_uint4(0u, 0u, 0u, 0u);
        }
#pragma unroll
        for (int sidx = 0; sidx < 3; sidx++) {
#pragma unroll
          for (int i = 0; i < 3; i++) {
            const uint32_t w[4] = {v[3 * sidx + i].x, v[3 * sidx + i].y, v[3 * sidx + i].z, v[3 * sidx + i].w};
#pragma unroll
            for (int k = 0; k < 4; k++) {
              own[8 * i + 2 * k]     += __uint_as_float(w[k] << 16);
              own[8 * i + 2 * k + 1] += __uint_as_float(w[k] & 0xffff0000u);
            }
          }
        }
      }
      stg_acquire();
      {
        const uint32_t st_base = wstg + (((lane >> 3) & 1) * 8 + (lane & 7)) * 32 + (lane >> 4) * 16;
#pragma unroll
        for (int jj = 0; jj < 3; jj++) {
          asm volatile("stmatrix.sync.aligned.m8n8.x4.shared.b16 [%0], {%1, %2, %3, %4};"
                       :: "r"(st_base + jj * 512), "r"(pack_bf16(own[8 * jj], own[8 * jj + 1])), "r"(pack_bf16(own[8 * jj + 2], own[8 * jj + 3])),
                          "r"(pack_bf16(own[8 * jj + 4], own[8 * jj + 5])), "r"(pack_bf16(own[8 * jj + 6], own[8 * jj + 7])) : "memory");
        }
        asm volatile("fence.proxy.async.shared::cta;" ::: "memory");
        __syncwarp();
        if (lane == 0) {
          const int a0 = split == 0 ? 0 : split == 1 ? 48 : split == 2 ? 80 : 128;
#pragma unroll
          for (int u = 0; u < 3; u++) {
            if (u < nown) {
              const int a = a0 + 16 * u;
              const int col = rank == 0 ? a : (a < 128 ? 192 + (a ^ 32) : 32 + a);
              tma_store_2d(&prm.out_st, wstg + u * 512, 640 * prob + 320 * (j8 & 1) + col, 192 * bp + 16 * warp);
            }
          }
          asm volatile("cp.async.bulk.commit_group;" ::: "memory");
          asm volatile("cp.async.bulk.wait_group.read 0;" ::: "memory");
        }
      }
      if (t == 0) prm.epoch[cta] = otarget;
    }
  }
}

typedef CUresult (*EncodeFn)(CUtensorMap*, CUtensorMapDataType, cuuint32_t, void*, const cuuint64_t*, const cuuint64_t*,
                             const cuuint32_t*, const cuuint32_t*, CUtensorMapInterleave, CUtensorMapSwizzle,
                             CUtensorMapL2promotion, CUtensorMapFloatOOBfill);

void make_map(EncodeFn enc, CUtensorMap* m, const void* ptr, int rank, const uint64_t* dims, const uint64_t* strides,
              const uint32_t* box, CUtensorMapSwizzle swz = CU_TENSOR_MAP_SWIZZLE_128B) {
  cuuint64_t d[3], s[2]; cuuint32_t b[3], e[3] = {1, 1, 1};
  for (int i = 0; i < rank; i++) { d[i] = dims[i]; b[i] = box[i]; }
  for (int i = 0; i + 1 < rank; i++) s[i] = strides[i];
  enc(m, CU_TENSOR_MAP_DATA_TYPE_BFLOAT16, rank, const_cast<void*>(ptr), d, s, b, e, CU_TENSOR_MAP_INTERLEAVE_NONE,
      swz, CU_TENSOR_MAP_L2_PROMOTION_L2_128B, CU_TENSOR_MAP_FLOAT_OOB_FILL_NONE);
}

}

extern "C" void kernel_launch(void* const* d_in, const int* in_sizes, int n_in, void* d_out, int out_size) {
  (void)in_sizes; (void)n_in; (void)out_size;
  static EncodeFn enc = nullptr;
  static void *o_ptr = nullptr, *part_ptr = nullptr, *ready_ptr = nullptr, *xflag_ptr = nullptr, *epoch_ptr = nullptr;
  if (!enc) {
    void* fn = nullptr; cudaDriverEntryPointQueryResult st;
    cudaGetDriverEntryPoint("cuTensorMapEncodeTiled", &fn, cudaEnableDefault, &st);
    enc = (EncodeFn)fn;
    cudaGetSymbolAddress(&o_ptr, g_O);
    cudaGetSymbolAddress(&part_ptr, g_part);
    cudaGetSymbolAddress(&ready_ptr, g_ready);
    cudaGetSymbolAddress(&xflag_ptr, g_xflag);
    cudaGetSymbolAddress(&epoch_ptr, g_epoch);
    cudaFuncSetAttribute(fused_attn_kernel, cudaFuncAttributeMaxDynamicSharedMemorySize, SMEM_BYTES);
  }
  Params prm;
  for (int p = 0; p < 2; p++) {
    const void* x = d_in[5 * p + 0]; const void* k = d_in[5 * p + 1]; const void* v = d_in[5 * p + 2];
    const void* wq = d_in[5 * p + 3]; const void* wo = d_in[5 * p + 4];
    { uint64_t d[2] = {640, 768}, s[1] = {1280};              uint32_t b[2] = {64, 96};    make_map(enc, &prm.x[p],  x,  2, d, s, b); }
    { uint64_t d[2] = {640, 768}, s[1] = {1280};              uint32_t b[2] = {64, 192};   make_map(enc, &prm.x1[p], x,  2, d, s, b); }
    { uint64_t d[3] = {64, 640, 96}, s[2] = {12288, 128};     uint32_t b[3] = {64, 64, 3}; make_map(enc, &prm.wq[p], wq, 3, d, s, b); }
    { uint64_t d[3] = {64, 24576, 3}, s[2] = {384, 128};      uint32_t b[3] = {64, 96, 3}; make_map(enc, &prm.k[p],  k,  3, d, s, b); }
    { uint64_t d[3] = {64, 24576, 3}, s[2] = {384, 128};      uint32_t b[3] = {64, 96, 1}; make_map(enc, &prm.k1[p], k,  3, d, s, b); }
    { uint64_t d[3] = {64, 24576, 3}, s[2] = {384, 128};      uint32_t b[3] = {64, 96, 3}; make_map(enc, &prm.v[p],  v,  3, d, s, b); }
    { uint64_t d[3] = {64, 24576, 3}, s[2] = {384, 128};      uint32_t b[3] = {64, 96, 1}; make_map(enc, &prm.v1[p], v,  3, d, s, b); }
    prm.kptr[p] = (const uint8_t*)k; prm.vptr[p] = (const uint8_t*)v;
    prm.wqptr[p] = (const uint8_t*)wq;
    { uint64_t d[2] = {640, 6144}, s[1] = {1280};             uint32_t b[2] = {64, 64};    make_map(enc, &prm.wo[p], wo, 2, d, s, b); }
  }
  { uint64_t d[2] = {6144, 1536}, s[1] = {12288};        uint32_t b[2] = {64, 16};    make_map(enc, &prm.o_st, o_ptr, 2, d, s, b); }
  { uint64_t d[2] = {6144, 1536}, s[1] = {12288};        uint32_t b[2] = {64, 96};    make_map(enc, &prm.o_ld, o_ptr, 2, d, s, b); }
  { uint64_t d[2] = {1280, 768}, s[1] = {2560};          uint32_t b[2] = {16, 16};    make_map(enc, &prm.out_st, d_out, 2, d, s, b, CU_TENSOR_MAP_SWIZZLE_NONE); }
  prm.part = (uint4*)part_ptr; prm.ready = (unsigned*)ready_ptr; prm.xflag = (unsigned*)xflag_ptr; prm.epoch = (unsigned*)epoch_ptr;
  fused_attn_kernel<<<128, NTHREADS, SMEM_BYTES>>>(prm);
}
```
